```python
import torch

def _softmax(x, axis=-1):
    return torch.softmax(x, dim=axis)
def _gelu(x):
    return torch.nn.functional.gelu(x, approximate="tanh")
def _silu(x):
    return torch.nn.functional.silu(x)
def _sigmoid(x):
    return torch.sigmoid(x)
def _layernorm(x, axis=-1, eps=1e-5):
    m = x.mean(dim=axis, keepdim=True)
    v = x.var(dim=axis, keepdim=True, unbiased=False)
    return (x - m) / torch.sqrt(v + eps)
def _scatter_add(tgt, idx, src, axis=0):
    return tgt.clone().index_add_(axis, idx, src)
def _segment_sum(src, seg, n):
    out = torch.zeros((n,) + src.shape[1:], dtype=src.dtype)
    return out.index_add_(0, seg, src)
def _pad(x, pw):
    flat = tuple(v for pair in reversed(pw) for v in pair)
    return torch.nn.functional.pad(x, flat)

kernel_name = 'standalone__detection_seg_fpn_lateral__vision'

def setup_inputs():

    _w = (lambda a: (lambda t: t.to(torch.bfloat16) if t.is_floating_point() else t)(torch.as_tensor(a)))
    H = W = (384 // 2) * 2
    C = 384
    k = 1
    return {
        "c_fine": _w((lambda *s: torch.randn(*s, dtype=torch.bfloat16) * 0.05)(1, H, W, C)),
        "p_coarse": _w((lambda *s: torch.randn(*s, dtype=torch.bfloat16) * 0.05)(1, H // 2, W // 2, C)),
        "w_lat": _w((lambda *s: torch.randn(*s, dtype=torch.bfloat16) * 0.05)(C, C)),
        "w_out": _w((lambda *s: torch.randn(*s, dtype=torch.bfloat16) * 0.05)(k, k, C, C)),
    }

def reference(c_fine, p_coarse, w_lat, w_out):
    B, H, W, C = c_fine.shape
    k = 1
    lat = torch.einsum("bhwc,cd->bhwd", c_fine, w_lat)
    up = (lambda x, n, axis: torch.repeat_interleave(x, n, dim=axis))((lambda x, n, axis: torch.repeat_interleave(x, n, dim=axis))(p_coarse, 2, axis=1), 2, axis=2)
    m = lat + up
    pad = k // 2
    mp = _pad(m, ((0, 0), (pad, pad), (pad, pad), (0, 0)))
    o = None
    for di in range(k):
        for dj in range(k):
            t = torch.einsum("bhwc,cd->bhwd", mp[:, di:di + H, dj:dj + W, :], w_out[di, dj])
            o = t if o is None else o + t
    return o
```

```cpp
#include <cuda_runtime.h>
#include <cuda_bf16.h>
#include <cuda.h>
#include <stdint.h>

namespace {

constexpr int C          = 384;
constexpr int HW         = 384;
constexpr int NPIX       = HW * HW;
constexpr int NCOARSE    = NPIX / 4;
constexpr int NSEG       = NCOARSE / 16;
constexpr int NJOBS      = 36;

constexpr int NSLOTS     = 10;
constexpr int MAXPAIRS   = 66;
constexpr int PF_LEAD    = 5;
constexpr int PF_LEAD0   = 17;
constexpr int PF_DECAY   = 10;
constexpr int PF_GAP     = 50;
constexpr int PF_GAP0    = 150;
constexpr int TMA_DELAY  = 0;
constexpr int PF_RATE    = 2;
constexpr int PF_SKIP0   = 0;
constexpr int PF_SKIP1   = 3;
constexpr int PF_FIRST   = 7;
constexpr int HOLD       = 200;
constexpr int JOBPRIO    = 1;
constexpr int PPF        = 0;
constexpr int WL0        = 2;
constexpr int WL1        = 3;
constexpr int WL2        = 6;
constexpr int WL3        = 6;
constexpr int WL4        = 8;
constexpr int WL5        = 8;
constexpr int W5MODE     = 2;
constexpr int W5N        = 32;
constexpr int W5T        = 4;
constexpr int W5MASK     = 9;
constexpr int W5FROM     = 6;
constexpr int GOV_START  = 14;
constexpr int GOV_SLACK  = 0;

constexpr int SLOT_BYTES  = 8192;
constexpr int WOUT_SLICE  = 320 * 128;
constexpr int OFF_WOUT    = 0;
constexpr int OFF_RING    = 3 * WOUT_SLICE;
constexpr int OFF_STAGE   = OFF_RING + NSLOTS * SLOT_BYTES;
constexpr int OFF_BAR     = OFF_STAGE + 3 * 8192;
constexpr int OFF_FULL    = OFF_BAR;
constexpr int OFF_EMPTY   = OFF_FULL + 8 * NSLOTS;
constexpr int OFF_WBAR    = OFF_EMPTY + 8 * NSLOTS;
constexpr int OFF_JBAR    = OFF_WBAR + 8;
constexpr int OFF_JB2     = OFF_JBAR + 8;
constexpr int OFF_PACE    = OFF_JB2 + 8;
constexpr int SMEM_BYTES  = OFF_PACE + 8;
static_assert(SMEM_BYTES <= 232448, "smem");
static_assert(NSLOTS >= 10, "the first tile (nine ring items) is requested in the prologue");

constexpr int NTHREADS = 512;
constexpr uint64_t POLICY_EVICT_FIRST  = 0x12F0000000000000ull;

__device__ uint4    g_wfrag[2 * 6 * 24 * 128];
__device__ unsigned g_epoch;
__device__ unsigned g_prog;
__device__ unsigned g_done;

#define TSTAMP(role, idx) do {} while (0)
#define TDUMP(role) do {} while (0)
#define LSTAMP(kind, n) do {} while (0)
__device__ __forceinline__ uint32_t smem_u32(const void* p) { return (uint32_t)__cvta_generic_to_shared(p); }

__device__ __forceinline__ void mbar_init(uint32_t bar, uint32_t cnt) {
    asm volatile("mbarrier.init.shared::cta.b64 [%0], %1;" ::"r"(bar), "r"(cnt) : "memory");
}
__device__ __forceinline__ void mbar_expect_tx(uint32_t bar, uint32_t bytes) {
    asm volatile("mbarrier.arrive.expect_tx.shared::cta.b64 _, [%0], %1;" ::"r"(bar), "r"(bytes) : "memory");
}
__device__ __forceinline__ void mbar_wait_bounded(uint32_t bar, uint32_t parity) {
    asm volatile(
        "{\n"
        ".reg .pred p;\n"
        ".reg .u32 n;\n"
        "mbarrier.try_wait.parity.shared::cta.b64 p, [%0], %1;\n"
        "@p bra DONE_%=;\n"
        "mov.u32 n, 0;\n"
        "WAIT_%=:\n"
        "mbarrier.try_wait.parity.shared::cta.b64 p, [%0], %1;\n"
        "@p bra DONE_%=;\n"
        "add.u32 n, n, 1;\n"
        "setp.lt.u32 p, n, 4000000;\n"
        "@p bra WAIT_%=;\n"
        "trap;\n"
        "DONE_%=:\n"
        "}\n" ::"r"(bar), "r"(parity) : "memory");
}
__device__ __forceinline__ void mbar_wait(uint32_t bar, uint32_t parity) {
    asm volatile(
        "{\n"
        ".reg .pred p;\n"
        "WAIT_%=:\n"
        "mbarrier.try_wait.parity.shared::cta.b64 p, [%0], %1;\n"
        "@!p bra WAIT_%=;\n"
        "}\n" ::"r"(bar), "r"(parity) : "memory");
}
__device__ __forceinline__ void mbar_arrive_cluster(uint32_t cluster_addr) {
    asm volatile("mbarrier.arrive.shared::cluster.b64 _, [%0];" ::"r"(cluster_addr) : "memory");
}
__device__ __forceinline__ uint32_t mapa(uint32_t addr, uint32_t rank) {
    uint32_t r;
    asm("mapa.shared::cluster.u32 %0, %1, %2;" : "=r"(r) : "r"(addr), "r"(rank));
    return r;
}
__device__ __forceinline__ void named_bar(int wg) {
    asm volatile("bar.sync %0, 128;" ::"r"(wg + 1) : "memory");
}

__device__ __forceinline__ void tma_load_2d(uint32_t dst, const CUtensorMap* tm, int c0, int c1, uint32_t bar) {
    asm volatile("cp.async.bulk.tensor.2d.shared::cluster.global.mbarrier::complete_tx::bytes [%0], [%1, {%2, %3}], [%4];"
                 ::"r"(dst), "l"(tm), "r"(c0), "r"(c1), "r"(bar) : "memory");
}
__device__ __forceinline__ void tma_load_3d(uint32_t dst, const CUtensorMap* tm, int c0, int c1, int c2, uint32_t bar) {
    asm volatile("cp.async.bulk.tensor.3d.shared::cluster.global.mbarrier::complete_tx::bytes [%0], [%1, {%2, %3, %4}], [%5];"
                 ::"r"(dst), "l"(tm), "r"(c0), "r"(c1), "r"(c2), "r"(bar) : "memory");
}
__device__ __forceinline__ void tma_load_5d(uint32_t dst, const CUtensorMap* tm, int c0, int c3, int c4, uint32_t bar) {
    asm volatile("cp.async.bulk.tensor.5d.shared::cluster.global.mbarrier::complete_tx::bytes [%0], [%1, {%2, 0, 0, %3, %4}], [%5];"
                 ::"r"(dst), "l"(tm), "r"(c0), "r"(c3), "r"(c4), "r"(bar) : "memory");
}
__device__ __forceinline__ void tma_load_2d_mc(uint32_t dst, const CUtensorMap* tm, int c0, int c1, uint32_t bar) {
    asm volatile("cp.async.bulk.tensor.2d.shared::cluster.global.mbarrier::complete_tx::bytes.multicast::cluster"
                 " [%0], [%1, {%2, %3}], [%4], %5;"
                 ::"r"(dst), "l"(tm), "r"(c0), "r"(c1), "r"(bar), "h"((uint16_t)3) : "memory");
}
__device__ __forceinline__ void tma_load_5d_mc(uint32_t dst, const CUtensorMap* tm, int c0, int c3, int c4, uint32_t bar) {
    asm volatile("cp.async.bulk.tensor.5d.shared::cluster.global.mbarrier::complete_tx::bytes.multicast::cluster"
                 " [%0], [%1, {%2, 0, 0, %3, %4}], [%5], %6;"
                 ::"r"(dst), "l"(tm), "r"(c0), "r"(c3), "r"(c4), "r"(bar), "h"((uint16_t)3) : "memory");
}
__device__ __forceinline__ void tma_store_2d(const CUtensorMap* tm, int c0, int c1, uint32_t src, uint64_t pol) {
    asm volatile("cp.async.bulk.tensor.2d.global.shared::cta.bulk_group.L2::cache_hint [%0, {%1, %2}], [%3], %4;"
                 ::"l"(tm), "r"(c0), "r"(c1), "r"(src), "l"(pol) : "memory");
}
__device__ __forceinline__ void prefetch_tmap(const CUtensorMap* tm) {
    asm volatile("prefetch.tensormap [%0];" ::"l"(tm) : "memory");
}

__device__ __forceinline__ void wg_fence()  { asm volatile("wgmma.fence.sync.aligned;" ::: "memory"); }
__device__ __forceinline__ void wg_commit() { asm volatile("wgmma.commit_group.sync.aligned;" ::: "memory"); }
template <int N> __device__ __forceinline__ void wg_wait() { asm volatile("wgmma.wait_group.sync.aligned %0;" ::"n"(N) : "memory"); }

#define ACC16(a)                                                                                              \
    "+f"(a[0]), "+f"(a[1]), "+f"(a[2]), "+f"(a[3]), "+f"(a[4]), "+f"(a[5]), "+f"(a[6]), "+f"(a[7]),           \
    "+f"(a[8]), "+f"(a[9]), "+f"(a[10]), "+f"(a[11]), "+f"(a[12]), "+f"(a[13]), "+f"(a[14]), "+f"(a[15])
#define ACC32(a)                                                                                              \
    ACC16(a),                                                                                                 \
    "+f"(a[16]), "+f"(a[17]), "+f"(a[18]), "+f"(a[19]), "+f"(a[20]), "+f"(a[21]), "+f"(a[22]), "+f"(a[23]),   \
    "+f"(a[24]), "+f"(a[25]), "+f"(a[26]), "+f"(a[27]), "+f"(a[28]), "+f"(a[29]), "+f"(a[30]), "+f"(a[31])
#define ACC16_STR "{%0, %1, %2, %3, %4, %5, %6, %7, %8, %9, %10, %11, %12, %13, %14, %15}"
#define ACC32_STR                                                                                             \
    "{%0, %1, %2, %3, %4, %5, %6, %7, %8, %9, %10, %11, %12, %13, %14, %15, "                                 \
    "%16, %17, %18, %19, %20, %21, %22, %23, %24, %25, %26, %27, %28, %29, %30, %31}"

template <int BOFF>
__device__ __forceinline__ void wgmma_rs(float (&d)[32], uint32_t a0, uint32_t a1, uint32_t a2, uint32_t a3, uint32_t db_lo) {
    asm volatile("{\n.reg .b64 db;\n.reg .b32 lo;\n"
                 "add.u32 lo, %36, %37;\nmov.b64 db, {lo, 0x40000040};\n"
                 "wgmma.mma_async.sync.aligned.m64n64k16.f32.bf16.bf16 " ACC32_STR
                 ", {%32, %33, %34, %35}, db, 1, -1, 1, 0;\n}"
                 : ACC32(d) : "r"(a0), "r"(a1), "r"(a2), "r"(a3), "r"(db_lo), "n"(BOFF));
}
template <int ACCUM, int AOFF, int BOFF>
__device__ __forceinline__ void wgmma_ss(float (&d)[32], uint32_t da_lo, uint32_t db_lo) {
    asm volatile("{\n.reg .b64 da, db;\n.reg .b32 lo;\n"
                 "add.u32 lo, %32, %35;\nmov.b64 da, {lo, 0x40000040};\n"
                 "add.u32 lo, %33, %36;\nmov.b64 db, {lo, 0x40000040};\n"
                 "wgmma.mma_async.sync.aligned.m64n64k16.f32.bf16.bf16 " ACC32_STR
                 ", da, db, %34, 1, 1, 1, 0;\n}"
                 : ACC32(d) : "r"(da_lo), "r"(db_lo), "n"(ACCUM), "n"(AOFF), "n"(BOFF));
}
template <int ACCUM, int AOFF, int BOFF>
__device__ __forceinline__ void wgmma_ss32(float (&d)[16], uint32_t da_lo, uint32_t db_lo) {
    asm volatile("{\n.reg .b64 da, db;\n.reg .b32 lo;\n"
                 "add.u32 lo, %16, %19;\nmov.b64 da, {lo, 0x40000040};\n"
                 "add.u32 lo, %17, %20;\nmov.b64 db, {lo, 0x40000040};\n"
                 "wgmma.mma_async.sync.aligned.m64n32k16.f32.bf16.bf16 " ACC16_STR
                 ", da, db, %18, 1, 1, 1, 0;\n}"
                 : ACC16(d) : "r"(da_lo), "r"(db_lo), "n"(ACCUM), "n"(AOFF), "n"(BOFF));
}
__device__ __forceinline__ uint32_t desc_lo(uint32_t addr) { return ((addr & 0x3FFFFu) >> 4) | (1u << 16); }
__device__ __forceinline__ uint32_t pack_bf16(float lo, float hi) {
    uint32_t r;
    asm("cvt.rn.bf16x2.f32 %0, %1, %2;" : "=r"(r) : "f"(hi), "f"(lo));
    return r;
}
__device__ __forceinline__ uint32_t pack_neg(float lo, float hi) {
    const uint32_t v = pack_bf16(lo, hi) ^ 0x80008000u;
    return v == 0u ? 0x80008000u : v;
}
__device__ __forceinline__ void stsm_x4_t(uint32_t addr, uint32_t r0, uint32_t r1, uint32_t r2, uint32_t r3) {
    asm volatile("stmatrix.sync.aligned.m8n8.x4.trans.shared.b16 [%0], {%1, %2, %3, %4};"
                 ::"r"(addr), "r"(r0), "r"(r1), "r"(r2), "r"(r3) : "memory");
}

struct Ring {
    uint32_t so;
    uint32_t ph;
    __device__ __forceinline__ void advance() {
        so += 8;
        if (so == NSLOTS * 8) { so = 0; ph ^= 1; }
    }
    __device__ __forceinline__ uint32_t prev() const { return so == 0 ? (NSLOTS - 1) * 8 : so - 8; }
    __device__ __forceinline__ uint32_t back(uint32_t k) const { return so >= k * 8 ? so - k * 8 : so + (NSLOTS - k) * 8; }
};

struct Ctx {
    uint32_t sbase;
    uint32_t db0;
    uint32_t empty_tgt;
    bool     signal;
};

template <int KC, bool RS>
__device__ __forceinline__ void chunk(float (&acc)[32], const uint32_t (&W)[96], uint32_t da0, const Ctx& cx, Ring& rg) {
    mbar_wait(cx.sbase + OFF_FULL + rg.so, rg.ph);
    const uint32_t db = cx.db0 + rg.so * 64;
    wg_fence();
    if (RS) {
        wgmma_rs<0>(acc, W[KC * 16 + 0],  W[KC * 16 + 1],  W[KC * 16 + 2],  W[KC * 16 + 3],  db);
        wgmma_rs<2>(acc, W[KC * 16 + 4],  W[KC * 16 + 5],  W[KC * 16 + 6],  W[KC * 16 + 7],  db);
        wgmma_rs<4>(acc, W[KC * 16 + 8],  W[KC * 16 + 9],  W[KC * 16 + 10], W[KC * 16 + 11], db);
        wgmma_rs<6>(acc, W[KC * 16 + 12], W[KC * 16 + 13], W[KC * 16 + 14], W[KC * 16 + 15], db);
    } else {
        wgmma_ss<(KC > 0), (KC * 4 + 0) * 128, 0>(acc, da0, db);
        wgmma_ss<1,        (KC * 4 + 1) * 128, 2>(acc, da0, db);
        wgmma_ss<1,        (KC * 4 + 2) * 128, 4>(acc, da0, db);
        wgmma_ss<1,        (KC * 4 + 3) * 128, 6>(acc, da0, db);
    }
    wg_commit();
    if (KC > 0) {
        wg_wait<1>();
        if (cx.signal) mbar_arrive_cluster(cx.empty_tgt + rg.prev());
    }
    rg.advance();
}

__device__ __forceinline__ void chunk_q5(float (&acc)[32], int wg, const Ctx& cx, Ring& rg) {
    Ring r = rg;
    mbar_wait(cx.sbase + OFF_FULL + r.so, r.ph);
    const uint32_t db = cx.db0 + r.so * 64;
    uint32_t da = 0;
#pragma unroll
    for (int g = 0; g < 3; g++) {
        r.advance();
        mbar_wait(cx.sbase + OFF_FULL + r.so, r.ph);
        if (g == wg) da = cx.db0 + r.so * 64;
    }
    r.advance();
    wg_fence();
    wgmma_ss<1, 0 * 128, 0>(acc, da, db);
    wgmma_ss<1, 1 * 128, 2>(acc, da, db);
    wgmma_ss<1, 2 * 128, 4>(acc, da, db);
    wgmma_ss<1, 3 * 128, 6>(acc, da, db);
    wg_commit();
    wg_wait<1>();
    if (cx.signal) mbar_arrive_cluster(cx.empty_tgt + rg.prev());
    rg = r;
}
__device__ __forceinline__ void finish_q(const Ctx& cx, const Ring& rg) {
    wg_wait<0>();
    if (cx.signal) {
        mbar_arrive_cluster(cx.empty_tgt + rg.back(4));
        mbar_arrive_cluster(cx.empty_tgt + rg.back(3));
        mbar_arrive_cluster(cx.empty_tgt + rg.back(2));
        mbar_arrive_cluster(cx.empty_tgt + rg.back(1));
    }
}

__global__ void __cluster_dims__(2, 1, 1) __launch_bounds__(NTHREADS, 1)
fpn_kernel(const __grid_constant__ CUtensorMap tm_c, const __grid_constant__ CUtensorMap tm_p,
           const __grid_constant__ CUtensorMap tm_wout, const __grid_constant__ CUtensorMap tm_wl3,
           const __grid_constant__ CUtensorMap tm_out, const __grid_constant__ CUtensorMap tm_p8,
           const __grid_constant__ CUtensorMap tm_w64,
           const __nv_bfloat16* __restrict__ c_ptr, const __nv_bfloat16* __restrict__ p_ptr,
           const __nv_bfloat16* __restrict__ wl_ptr, const __nv_bfloat16* __restrict__ wo_ptr, const int maxfine)
{
    extern __shared__ __align__(1024) uint8_t smem[];
    const uint32_t sbase = smem_u32(smem);
    const int tid   = threadIdx.x;
    const int warp  = __shfl_sync(0xffffffffu, tid >> 5, 0);
    const int lane  = tid & 31;
    const int rank  = blockIdx.x & 1;
    const int pair  = blockIdx.x >> 1;
    const int npair = gridDim.x >> 1;

    const int nfine = maxfine - ((maxfine - 1) * npair + pair >= NSEG);
    auto seg_row = [](int g) { const int y = g / 12; return y * (2 * HW) + (g - y * 12) * 32; };

    if (warp == 13) {
        for (int i = blockIdx.x * 32 + lane; i < 2 * C * C * 2 / 128; i += gridDim.x * 32) {
            const char* p = (i < C * C * 2 / 128) ? (const char*)wl_ptr + i * 128 : (const char*)wo_ptr + (i - C * C * 2 / 128) * 128;
            asm volatile("prefetch.global.L2 [%0];" ::"l"(p) : "memory");
        }
        if (PPF) {
#pragma unroll
            for (int k = 0; k < 6; k++)
                asm volatile("prefetch.global.L2 [%0];" ::"l"((const char*)p_ptr + (size_t)((2 * rank + k / 3) * npair + pair) * (16 * C * 2) + lane * 128 + (k % 3) * 4096) : "memory");
        }
        if (lane == 0) TSTAMP(3, 7);
    }
    if (tid == 448) { prefetch_tmap(&tm_wout); prefetch_tmap(&tm_wl3); prefetch_tmap(&tm_w64); prefetch_tmap(&tm_p8); }
    if (tid == 480) { prefetch_tmap(&tm_c); prefetch_tmap(&tm_p); prefetch_tmap(&tm_out); }
    if (warp == 12) {
        if (lane == 0) {
            for (int s = 0; s < NSLOTS; s++) {
                mbar_init(sbase + OFF_FULL + s * 8, 1);
                mbar_init(sbase + OFF_EMPTY + s * 8, 6);
            }
            mbar_init(sbase + OFF_WBAR, 1);
            mbar_init(sbase + OFF_JB2, 1);
            mbar_init(sbase + OFF_JBAR, 1);
            if (pair >= NJOBS) asm volatile("mbarrier.arrive.shared::cta.b64 _, [%0];" ::"r"(sbase + OFF_FULL) : "memory");
            asm volatile("mbarrier.arrive.shared::cta.b64 _, [%0];" ::"r"(sbase + OFF_FULL + 8) : "memory");
            asm volatile("mbarrier.arrive.shared::cta.b64 _, [%0];" ::"r"(sbase + OFF_FULL + 16) : "memory");
            asm volatile("st.volatile.shared.u32 [%0], %1;" ::"r"(sbase + OFF_PACE), "r"(6) : "memory");
            asm volatile("fence.mbarrier_init.release.cluster;" ::: "memory");
            asm volatile("fence.proxy.async.shared::cta;" ::: "memory");
        }
        __syncwarp();
        asm volatile("bar.arrive 5, 416;" ::: "memory");
        if (lane == 0) TSTAMP(3, 4);
    }
    asm volatile("barrier.cluster.arrive.relaxed.aligned;" ::: "memory");
    if (warp >= 12) {
        asm volatile("setmaxnreg.dec.sync.aligned.u32 32;");
        if (tid == 384) {
            if (TMA_DELAY) __nanosleep(TMA_DELAY);
            TSTAMP(3, 5);
            const int g0 = pair % 3, g1 = (pair + 1) % 3, g2 = (pair + 2) % 3;
            mbar_expect_tx(sbase + OFF_WBAR, WOUT_SLICE);
            tma_load_2d(sbase + OFF_WOUT + g0 * WOUT_SLICE,         &tm_wout, rank * 192 + g0 * 64, 0,   sbase + OFF_WBAR);
            tma_load_2d(sbase + OFF_WOUT + g0 * WOUT_SLICE + 20480, &tm_wout, rank * 192 + g0 * 64, 160, sbase + OFF_WBAR);
            mbar_expect_tx(sbase + OFF_JBAR, 8192);
            tma_load_2d(sbase + OFF_STAGE + g0 * 8192, &tm_w64, rank * 192 + g0 * 64, 320, sbase + OFF_JBAR);
            if (pair < NJOBS) {
                mbar_expect_tx(sbase + OFF_FULL, 6 * 4096);
                tma_load_3d(sbase + OFF_RING, &tm_wl3, 0, (pair / 3) * 32, 0, sbase + OFF_FULL);
            }
            if (HOLD == 1) { mbar_wait_bounded(sbase + OFF_WBAR, 0); }
            if (HOLD == 2) { mbar_wait_bounded(sbase + OFF_WBAR, 0); mbar_wait_bounded(sbase + OFF_FULL, 0); }
            if (HOLD > 9) __nanosleep(HOLD);
            TSTAMP(3, 6);
            if (HOLD >= 3 && HOLD <= 5) {
#pragma unroll 1
                for (int kc = 0; kc < 6; kc++) {
                    const uint32_t bar = sbase + OFF_FULL + (3 + kc) * 8;
                    mbar_expect_tx(bar, 3 * SLOT_BYTES);
                    tma_load_5d(sbase + OFF_RING + (3 + kc) * SLOT_BYTES, &tm_p8, kc * 64, pair * 2, 0, bar);
                }
                if (HOLD == 3) mbar_wait_bounded(sbase + OFF_WBAR, 0);
                if (HOLD == 5) __nanosleep(200);
            }
#pragma unroll 1
            for (int kc = 0; kc < 6; kc++) {
                const uint32_t bar = sbase + OFF_FULL + (3 + kc) * 8;
                if (!(HOLD >= 3 && HOLD <= 5)) {
                    mbar_expect_tx(bar, 3 * SLOT_BYTES);
                    tma_load_5d(sbase + OFF_RING + (3 + kc) * SLOT_BYTES, &tm_p8, kc * 64, pair * 2, 0, bar);
                }
                tma_load_2d(kc < 5 ? sbase + OFF_WOUT + g1 * WOUT_SLICE + kc * 8192 : sbase + OFF_STAGE + g1 * 8192,
                            &tm_w64, rank * 192 + g1 * 64, kc * 64, bar);
                tma_load_2d(kc < 5 ? sbase + OFF_WOUT + g2 * WOUT_SLICE + kc * 8192 : sbase + OFF_STAGE + g2 * 8192,
                            &tm_w64, rank * 192 + g2 * 64, kc * 64, bar);
            }
        }
        if (tid == 384) TSTAMP(3, 1);
        __syncwarp();
        asm volatile("barrier.cluster.wait.aligned;" ::: "memory");
        if (warp == 12) {
            if (lane == 0) {
                TSTAMP(3, 2);
                const uint32_t dst0 = sbase + OFF_RING + rank * 4096;
                uint32_t so = 9 * 8, ph = 1, step = 6;
                LSTAMP(0, 0);
                auto acquire = [&](uint32_t& bar, uint32_t& dst) {
                    bar = sbase + OFF_FULL + so;
                    dst = dst0 + so * (SLOT_BYTES / 8);
                    mbar_wait_bounded(sbase + OFF_EMPTY + so, ph);
                    mbar_expect_tx(bar, SLOT_BYTES);
                };
                auto advance = [&]() {
                    so += 8;
                    if (so == NSLOTS * 8) { so = 0; ph ^= 1; }
                    step++;
                    asm volatile("st.volatile.shared.u32 [%0], %1;" ::"r"(sbase + OFF_PACE), "r"(step) : "memory");
                };
                unsigned mytiles = 0, seen = 0;
                const unsigned maxtiles = maxfine + (maxfine - 1) / 4;
                auto govern = [&]() {
                    if (rank == 0) {
                        unsigned spins = 0;
                        while (mytiles >= GOV_START && (int)(mytiles * npair - seen) > GOV_SLACK && ++spins < 100000u)
                            asm volatile("ld.relaxed.gpu.global.u32 %0, [%1];" : "=r"(seen) : "l"(&g_prog) : "memory");
                        mytiles++;
                        asm volatile("red.relaxed.gpu.global.add.u32 [%0], 1;" ::"l"(&g_prog) : "memory");
                        asm volatile("ld.relaxed.gpu.global.u32 %0, [%1];" : "=r"(seen) : "l"(&g_prog) : "memory");
                    }
                };
#pragma unroll 1
                for (int j = 0; j < nfine; j++) {
                    if ((j & 3) == 0 && j > 0) {
                        const int jc = (j + 2 * rank < nfine) ? j + 2 * rank : maxfine;
                        govern();
#pragma unroll
                        for (int kc = 0; kc < 6; kc++) {
                            uint32_t bar, dst;
                            acquire(bar, dst);
                            tma_load_5d_mc(dst, &tm_p, kc * 64, pair * 2, jc, bar);
                            advance();
                        }
#pragma unroll
                        for (int g = 0; g < 3; g++) {
                            uint32_t bar, dst;
                            acquire(bar, dst);
                            tma_load_2d(dst - rank * 4096, &tm_w64, rank * 192 + g * 64, 320, bar);
                            so += 8;
                            if (so == NSLOTS * 8) { so = 0; ph ^= 1; }
                        }
                    }
                    const int row = seg_row(j * npair + pair) + rank * HW;
                    govern();
#pragma unroll
                    for (int kc = 0; kc < 6; kc++) {
                        uint32_t bar, dst;
                        acquire(bar, dst);
                        tma_load_2d_mc(dst, &tm_c, kc * 64, row, bar);
                        advance();
                    }
                }
                if (rank == 0) {
                    if (mytiles < maxtiles) asm volatile("red.relaxed.gpu.global.add.u32 [%0], %1;" ::"l"(&g_prog), "r"(maxtiles - mytiles) : "memory");
                }
                for (int s = 0; s < NSLOTS; s++) {
                    mbar_wait_bounded(sbase + OFF_EMPTY + so, ph);
                    so += 8;
                    if (so == NSLOTS * 8) { so = 0; ph ^= 1; }
                }
                TSTAMP(3, 3); TDUMP(3);
                const unsigned old = atomicAdd(&g_done, 1u);
                if (old == gridDim.x - 1) { g_done = 0; g_prog = 0; g_epoch = g_epoch + 1; }
            }
        } else if (warp == 13) {
            const int ntiles = nfine + (nfine + 3) / 4;
            uint32_t sink = 0, pv = 0;
#pragma unroll 1
            for (int i = 1; i < ntiles; i++) {
                const int k5 = i / 5, t = i - k5 * 5;
                const char *b0, *b1;
                if (t == 0) {
                    const int g = min((4 * k5 + 2 * rank) * npair + pair, NSEG - 1);
                    b0 = (const char*)p_ptr + (size_t)g * (16 * C * 2);
                    b1 = (const char*)p_ptr + (size_t)min(g + npair, NSEG - 1) * (16 * C * 2);
                } else {
                    b0 = (const char*)c_ptr + (size_t)(seg_row((4 * k5 + t - 1) * npair + pair) + rank * HW) * (C * 2);
                    b1 = b0 + 16 * C * 2;
                }
                const int extra = PF_LEAD0 - PF_LEAD - (i > PF_DECAY ? (i - PF_DECAY) * PF_RATE / 2 : 0);
                int need = 6 * i - PF_LEAD - (extra > 0 ? extra : 0);
                if (need < PF_FIRST) need = PF_FIRST;
                unsigned spins = 0;
                while (true) {
                    uint32_t v;
                    asm volatile("ld.volatile.shared.u32 %0, [%1];" : "=r"(v) : "r"(sbase + OFF_PACE) : "memory");
                    if ((int)v >= need || ++spins > 4000000u) break;
                    __nanosleep(20);
                }
                if (lane == 0) LSTAMP(2, i);
                if (i < PF_SKIP0 || i >= PF_SKIP1)
#pragma unroll
                for (int k = 0; k < 6; k++) {
                    asm volatile("prefetch.global.L2 [%0];" ::"l"((k < 3 ? b0 : b1) + lane * 128 + (k % 3) * 4096) : "memory");
                    __nanosleep(need == PF_FIRST ? PF_GAP0 : PF_GAP);
                }
                if (W5MODE == 0) {
                if (t == 0) {
#pragma unroll
                    for (int k = 0; k < 6; k++) {
                        const int idx = k * 32 + lane;
                        asm volatile("prefetch.global.L2 [%0];" ::"l"((const char*)wo_ptr + (320 + idx / 3) * (C * 2) + rank * 384 + (idx % 3) * 128) : "memory");
                    }
                }
                } else if (W5MODE == 2 || W5MODE == 3) {
                    const int idx = ((pair + i * 5) % (192 / W5N)) * W5N + lane;
                    if (lane < W5N && ((W5MASK >> t) & 1) && i >= W5FROM) {
                        sink ^= pv;
                        asm volatile("ld.global.cg.u32 %0, [%1];" : "=r"(pv) : "l"((const char*)wo_ptr + (320 + idx / 3) * (C * 2) + rank * 384 + (idx % 3) * 128) : "memory");
                    }
                } else if (W5MODE == 4) {
                    const int idx = (pair % 6) * 32 + lane;
                    if (t == W5T)
                        asm volatile("prefetch.global.L2 [%0];" ::"l"((const char*)wo_ptr + (320 + idx / 3) * (C * 2) + rank * 384 + (idx % 3) * 128) : "memory");
                }
            }
            asm volatile("st.volatile.shared.u32 [%0], %1;" ::"r"(sbase + OFF_PACE + 4), "r"(sink ^ pv) : "memory");
        }
    } else {
        asm volatile("setmaxnreg.inc.sync.aligned.u32 160;");
        uint32_t par;
        asm volatile("ld.relaxed.gpu.global.u32 %0, [%1];" : "=r"(par) : "l"(&g_epoch) : "memory");
        asm volatile("bar.sync 5, 416;" ::: "memory");
        const int wg   = warp >> 2;
        const int wtid = tid & 127;
        Ctx cx;
        cx.sbase     = sbase;
        cx.db0       = desc_lo(sbase + OFF_RING);
        cx.empty_tgt = mapa(sbase + OFF_EMPTY, warp & 1);
        cx.signal    = (lane == 0) && ((warp & 3) < 2);
        const uint32_t da0 = desc_lo(sbase + OFF_WOUT + wg * WOUT_SLICE);
        const int cb = rank * 3 + wg;

        float    acc[32];
        uint32_t qp[16];
        uint32_t W[96];
        Ring rg{0u, 0u};

        const uint32_t da5 = desc_lo(sbase + OFF_STAGE + wg * 8192) - 20 * 128;

        if (wtid == 0) TSTAMP(wg, 0);
        {
            uint32_t jph = 0;
            for (int job = pair; job < NJOBS; job += npair) {
                if (job % 3 == wg) {
                    if (job != pair) {
                        named_bar(wg);
                        if (wtid == 0) {
                            mbar_expect_tx(sbase + OFF_JB2, 6 * 4096);
                            tma_load_3d(sbase + OFF_RING, &tm_wl3, 0, (job / 3) * 32, 0, sbase + OFF_JB2);
                        }
                        for (int kc = 0; kc < 6; kc++) mbar_wait(sbase + OFF_FULL + (3 + kc) * 8, 0);
                        mbar_wait(sbase + OFF_JB2, jph);
                    }
                    mbar_wait(sbase + OFF_WBAR, 0);
                    mbar_wait(sbase + OFF_JBAR, 0);
                    mbar_wait(sbase + OFF_FULL, 0);
                    if (wtid == 0) TSTAMP(wg, 47);
                    float ja[16];
                    wg_fence();
#define JOBK(k) wgmma_ss32<((k) > 0), (k) * 128, ((k) >> 2) * 256 + ((k) & 3) * 2>(ja, (k) < 20 ? da0 : da5, cx.db0);
                    JOBK(0)  JOBK(1)  JOBK(2)  JOBK(3)  JOBK(4)  JOBK(5)  JOBK(6)  JOBK(7)
                    JOBK(8)  JOBK(9)  JOBK(10) JOBK(11) JOBK(12) JOBK(13) JOBK(14) JOBK(15)
                    JOBK(16) JOBK(17) JOBK(18) JOBK(19) JOBK(20) JOBK(21) JOBK(22) JOBK(23)
#undef JOBK
                    wg_commit();
                    wg_wait<0>();
                    if (wtid == 0) TSTAMP(wg, 48);
                    const int fidx = (cb * 24 + (job / 3) * 2) * 128 + wtid;
                    uint4* dst = g_wfrag + (par & 1) * (6 * 24 * 128) + fidx;
#pragma unroll
                    for (int i = 0; i < 2; i++) {
                        asm volatile("st.relaxed.gpu.global.v4.u32 [%0], {%1, %2, %3, %4};" ::"l"(dst + i * 128),
                                     "r"(pack_neg(ja[8 * i + 0], ja[8 * i + 1])), "r"(pack_neg(ja[8 * i + 2], ja[8 * i + 3])),
                                     "r"(pack_neg(ja[8 * i + 4], ja[8 * i + 5])), "r"(pack_neg(ja[8 * i + 6], ja[8 * i + 7])) : "memory");
                    }
                }
                if (job % 3 == wg && wtid == 0) TSTAMP(wg, 49);
                if (job + npair < NJOBS) asm volatile("bar.sync 4, 384;" ::: "memory");
                if (job != pair) jph ^= 1;
            }
        }

        par &= 1;
        if (JOBPRIO && pair < NJOBS) asm volatile("bar.sync 6, 384;" ::: "memory");
        if (wtid == 0) TSTAMP(wg, 1);
        asm volatile("barrier.cluster.wait.aligned;" ::: "memory");

        if (cx.signal) {
            mbar_arrive_cluster(cx.empty_tgt);
            mbar_arrive_cluster(cx.empty_tgt + 8);
            mbar_arrive_cluster(cx.empty_tgt + 16);
        }
        rg.so = 3 * 8;

        const uint4* wsrc = g_wfrag + (par * 6 + cb) * (24 * 128) + wtid;
        auto load_w = [&](int kc) {
#pragma unroll
            for (int s = 4 * kc; s < 4 * kc + 4; s++) {
                asm volatile("ld.relaxed.gpu.global.v4.u32 {%0, %1, %2, %3}, [%4];"
                             : "=r"(W[4 * s]), "=r"(W[4 * s + 1]), "=r"(W[4 * s + 2]), "=r"(W[4 * s + 3])
                             : "l"(wsrc + s * 128) : "memory");
            }
        };
        auto load_at = [&](int pos) {
            if (WL0 == pos) load_w(0);
            if (WL1 == pos) load_w(1);
            if (WL2 == pos) load_w(2);
            if (WL3 == pos) load_w(3);
            if (WL4 == pos) load_w(4);
            if (WL5 == pos) load_w(5);
        };
        auto check_w = [&](int kc) {
            uint32_t* w = W + 16 * kc;
            asm volatile(
                "{\n.reg .pred p;\n.reg .u32 m, n;\n"
                "mov.u32 n, 0;\n"
                "CHK_%=:\n"
                "min.u32 m, %0, %1;\n min.u32 m, m, %2;\n min.u32 m, m, %3;\n min.u32 m, m, %4;\n min.u32 m, m, %5;\n"
                "min.u32 m, m, %6;\n min.u32 m, m, %7;\n min.u32 m, m, %8;\n min.u32 m, m, %9;\n min.u32 m, m, %10;\n"
                "min.u32 m, m, %11;\n min.u32 m, m, %12;\n min.u32 m, m, %13;\n min.u32 m, m, %14;\n min.u32 m, m, %15;\n"
                "setp.ne.u32 p, m, 0;\n"
                "vote.sync.all.pred p, p, 0xffffffff;\n"
                "@p bra.uni OK_%=;\n"
                "add.u32 n, n, 1;\n"
                "setp.gt.u32 p, n, 5000000;\n"
                "@p bra.uni OK_%=;\n"
                "ld.relaxed.gpu.global.v4.u32 {%0, %1, %2, %3}, [%16];\n"
                "ld.relaxed.gpu.global.v4.u32 {%4, %5, %6, %7}, [%16 + 2048];\n"
                "ld.relaxed.gpu.global.v4.u32 {%8, %9, %10, %11}, [%16 + 4096];\n"
                "ld.relaxed.gpu.global.v4.u32 {%12, %13, %14, %15}, [%16 + 6144];\n"
                "bra.uni CHK_%=;\n"
                "OK_%=:\n}"
                : "+r"(w[0]), "+r"(w[1]), "+r"(w[2]), "+r"(w[3]), "+r"(w[4]), "+r"(w[5]), "+r"(w[6]), "+r"(w[7]),
                  "+r"(w[8]), "+r"(w[9]), "+r"(w[10]), "+r"(w[11]), "+r"(w[12]), "+r"(w[13]), "+r"(w[14]), "+r"(w[15])
                : "l"(wsrc + kc * 512) : "memory");
        };
        {
            if (wg == pair % 3) mbar_wait(sbase + OFF_WBAR, 0);
            chunk<0, false>(acc, W, da0, cx, rg);
            if (wtid == 0) TSTAMP(wg, 50);
            load_at(0);
            chunk<1, false>(acc, W, da0, cx, rg);
            load_at(1);
            chunk<2, false>(acc, W, da0, cx, rg);
            if (wtid == 0) TSTAMP(wg, 51);
            load_at(2);
            chunk<3, false>(acc, W, da0, cx, rg);
            load_at(3);
            chunk<4, false>(acc, W, da0, cx, rg);
            if (wtid == 0) TSTAMP(wg, 52);
            load_at(4);
            if (wg == pair % 3) mbar_wait(sbase + OFF_JBAR, 0);
            chunk<5, false>(acc, W, da5, cx, rg);
            load_at(5);
            wg_wait<0>();
            if (cx.signal) mbar_arrive_cluster(cx.empty_tgt + rg.prev());
#pragma unroll
            for (int j = 0; j < 16; j++) qp[j] = pack_bf16(acc[2 * j], acc[2 * j + 1]);
            if (wtid == 0) TSTAMP(wg, 2);
        }

        const uint32_t stage = sbase + OFF_STAGE + wg * 8192;
        const uint32_t st_addr = stage + (((lane >> 4) * 8 + (lane & 7)) << 7)
                               + (((((warp & 3) << 1) | ((lane >> 3) & 1)) ^ (lane & 7)) << 4);
        auto flush_part = [&](int row, int part) {
            if (part == 0) {
                asm volatile("fence.proxy.async.shared::cta;" ::: "memory");
                named_bar(wg);
            }
            if (wtid == 0) {
                tma_store_2d(&tm_out, cb * 64, row + (part >> 1) * HW + (part & 1) * 16, stage + part * 2048, POLICY_EVICT_FIRST);
                asm volatile("cp.async.bulk.commit_group;" ::: "memory");
            }
        };

        auto init_acc = [&]() {
#pragma unroll
            for (int b = 0; b < 2; b++) {
#pragma unroll
                for (int h = 0; h < 2; h++) {
                    const uint32_t q = qp[b * 2 + h];
                    float lo, hi;
                    asm volatile("shl.b32 %0, %1, 16;" : "=f"(lo) : "r"(q));
                    asm volatile("and.b32 %0, %1, 0xffff0000;" : "=f"(hi) : "r"(q));
#pragma unroll
                    for (int dy = 0; dy < 2; dy++) {
                        acc[16 * dy + 8 * b + 2 * h]         = lo;
                        acc[16 * dy + 8 * b + 2 * h + 1]     = lo;
                        acc[16 * dy + 8 * b + 4 + 2 * h]     = hi;
                        acc[16 * dy + 8 * b + 4 + 2 * h + 1] = hi;
                    }
                }
            }
#pragma unroll
            for (int i = 0; i < 12; i++) qp[i] = qp[i + 4];
        };
        auto stage_tile = [&]() {
            wg_wait<0>();
            if (cx.signal) mbar_arrive_cluster(cx.empty_tgt + rg.prev());
#pragma unroll
            for (int i = 0; i < 8; i += 2) {
                stsm_x4_t(st_addr + i * 1024,
                          pack_bf16(acc[4 * i + 0], acc[4 * i + 1]), pack_bf16(acc[4 * i + 2], acc[4 * i + 3]),
                          pack_bf16(acc[4 * i + 4], acc[4 * i + 5]), pack_bf16(acc[4 * i + 6], acc[4 * i + 7]));
            }
        };

        init_acc();
        check_w(0);
        if (wtid == 0) TSTAMP(wg, 3);
        chunk<0, true>(acc, W, da0, cx, rg);
        load_at(6);
        check_w(1);
        chunk<1, true>(acc, W, da0, cx, rg);
        load_at(7);
        check_w(2);
        chunk<2, true>(acc, W, da0, cx, rg);
        load_at(8);
        check_w(3);
        chunk<3, true>(acc, W, da0, cx, rg);
        load_at(9);
        check_w(4);
        chunk<4, true>(acc, W, da0, cx, rg);
        check_w(5);
        if (wtid == 0) TSTAMP(wg, 4);
        chunk<5, true>(acc, W, da0, cx, rg);
        named_bar(wg);
        stage_tile();

        int prow = seg_row(pair);
#pragma unroll 1
        for (int j = 1; j < nfine; j++) {
            const bool pend = (j & 3) != 0;
            if (!pend) {
                chunk<0, false>(acc, W, da0, cx, rg);
                flush_part(prow, 0);
                chunk<1, false>(acc, W, da0, cx, rg);
                chunk<2, false>(acc, W, da0, cx, rg);
                flush_part(prow, 1);
                chunk<3, false>(acc, W, da0, cx, rg);
                chunk<4, false>(acc, W, da0, cx, rg);
                flush_part(prow, 2);
                chunk_q5(acc, wg, cx, rg);
                flush_part(prow, 3);
                finish_q(cx, rg);
#pragma unroll
                for (int i = 0; i < 16; i++) qp[i] = pack_bf16(acc[2 * i], acc[2 * i + 1]);
            }
            init_acc();
            chunk<0, true>(acc, W, da0, cx, rg);
            if (pend) flush_part(prow, 0);
            chunk<1, true>(acc, W, da0, cx, rg);
            if (pend) flush_part(prow, 1);
            chunk<2, true>(acc, W, da0, cx, rg);
            chunk<3, true>(acc, W, da0, cx, rg);
            if (pend) flush_part(prow, 2);
            chunk<4, true>(acc, W, da0, cx, rg);
            if (pend) flush_part(prow, 3);
            chunk<5, true>(acc, W, da0, cx, rg);
            prow = seg_row(j * npair + pair);
            if (wtid == 0) asm volatile("cp.async.bulk.wait_group.read 0;" ::: "memory");
            named_bar(wg);
            stage_tile();
        }
#pragma unroll
        for (int part = 0; part < 4; part++) flush_part(prow, part);
        for (int job = pair; job < NJOBS; job += npair) {
            if (job % 3 == wg) {
                uint4* clr = g_wfrag + (par ^ 1) * (6 * 24 * 128) + (cb * 24 + (job / 3) * 2) * 128 + wtid;
                clr[0]   = make_uint4(0u, 0u, 0u, 0u);
                clr[128] = make_uint4(0u, 0u, 0u, 0u);
            }
        }
        if (wtid == 0) asm volatile("cp.async.bulk.wait_group.read 0;" ::: "memory");
        if (wtid == 0) { TSTAMP(wg, 45); TDUMP(wg); }
    }
}

typedef CUresult (*EncodeFn)(CUtensorMap*, CUtensorMapDataType, cuuint32_t, void*, const cuuint64_t*, const cuuint64_t*,
                             const cuuint32_t*, const cuuint32_t*, CUtensorMapInterleave, CUtensorMapSwizzle,
                             CUtensorMapL2promotion, CUtensorMapFloatOOBfill);

void encode(EncodeFn fn, CUtensorMap* tm, const void* ptr, int rank, const cuuint64_t* dims, const cuuint64_t* strides,
            const cuuint32_t* box) {
    const cuuint32_t es[5] = {1, 1, 1, 1, 1};
    fn(tm, CU_TENSOR_MAP_DATA_TYPE_BFLOAT16, (cuuint32_t)rank, const_cast<void*>(ptr), dims, strides, box, es,
       CU_TENSOR_MAP_INTERLEAVE_NONE, CU_TENSOR_MAP_SWIZZLE_128B, CU_TENSOR_MAP_L2_PROMOTION_NONE,
       CU_TENSOR_MAP_FLOAT_OOB_FILL_NONE);
}

}

extern "C" void kernel_launch(void* const* d_in, const int* in_sizes, int n_in, void* d_out, int out_size) {
    (void)in_sizes; (void)n_in; (void)out_size;
    const __nv_bfloat16* c_fine   = (const __nv_bfloat16*)d_in[0];
    const __nv_bfloat16* p_coarse = (const __nv_bfloat16*)d_in[1];
    const __nv_bfloat16* w_lat    = (const __nv_bfloat16*)d_in[2];
    const __nv_bfloat16* w_out    = (const __nv_bfloat16*)d_in[3];

    static EncodeFn fn = nullptr;
    static int grid = 0;
    if (!fn) {
        void* p = nullptr;
        cudaDriverEntryPointQueryResult qr;
        cudaGetDriverEntryPoint("cuTensorMapEncodeTiled", &p, cudaEnableDefault, &qr);
        fn = (EncodeFn)p;
        cudaFuncSetAttribute(fpn_kernel, cudaFuncAttributeMaxDynamicSharedMemorySize, SMEM_BYTES);
        cudaLaunchConfig_t cfg = {};
        cfg.gridDim = dim3(2); cfg.blockDim = dim3(NTHREADS); cfg.dynamicSmemBytes = SMEM_BYTES;
        cudaLaunchAttribute at[1];
        at[0].id = cudaLaunchAttributeClusterDimension;
        at[0].val.clusterDim.x = 2; at[0].val.clusterDim.y = 1; at[0].val.clusterDim.z = 1;
        cfg.attrs = at; cfg.numAttrs = 1;
        int ncl = 0;
        if (cudaOccupancyMaxActiveClusters(&ncl, fpn_kernel, &cfg) != cudaSuccess || ncl < 1) ncl = 1;
        if (ncl >= MAXPAIRS) ncl = MAXPAIRS;
        else while ((NSEG / 4) % ncl) ncl--;
        grid = 2 * ncl;
    }

    CUtensorMap tm_c, tm_p, tm_wout, tm_wl3, tm_out, tm_p8, tm_w64;
    {
        const cuuint64_t dims[2] = {(cuuint64_t)C, (cuuint64_t)NPIX};
        const cuuint64_t str[1]  = {(cuuint64_t)C * 2};
        const cuuint32_t box_in[2]  = {64, 32};
        const cuuint32_t box_out[2] = {64, 16};
        encode(fn, &tm_c, c_fine, 2, dims, str, box_in);
        encode(fn, &tm_out, d_out, 2, dims, str, box_out);
    }
    {
        const int np = grid / 2;
        const cuuint64_t dims[5] = {(cuuint64_t)C, 2, 4, (cuuint64_t)(2 * np), (cuuint64_t)((NSEG + np - 1) / np)};
        const cuuint64_t str[4]  = {(cuuint64_t)4 * C * 2, (cuuint64_t)C * 2, (cuuint64_t)8 * C * 2, (cuuint64_t)np * 16 * C * 2};
        const cuuint32_t box[5]  = {64, 2, 4, 2, 2};
        encode(fn, &tm_p, p_coarse, 5, dims, str, box);
        const cuuint32_t box8[5] = {64, 2, 4, 2, 4};
        encode(fn, &tm_p8, p_coarse, 5, dims, str, box8);
    }
    {
        const cuuint64_t dims[2] = {(cuuint64_t)C, (cuuint64_t)C};
        const cuuint64_t str[1]  = {(cuuint64_t)C * 2};
        const cuuint32_t box_o[2] = {64, 160};
        encode(fn, &tm_wout, w_out, 2, dims, str, box_o);
        const cuuint32_t box_k[2] = {64, 64};
        encode(fn, &tm_w64, w_out, 2, dims, str, box_k);
    }
    {
        const cuuint64_t dims[3] = {64, (cuuint64_t)C, 6};
        const cuuint64_t str[2]  = {(cuuint64_t)C * 2, 128};
        const cuuint32_t box[3]  = {64, 32, 6};
        encode(fn, &tm_wl3, w_lat, 3, dims, str, box);
    }
    fpn_kernel<<<grid, NTHREADS, SMEM_BYTES>>>(tm_c, tm_p, tm_wout, tm_wl3, tm_out, tm_p8, tm_w64, c_fine, p_coarse, w_lat, w_out,
                                               (NSEG + grid / 2 - 1) / (grid / 2));
}
```

```cpp
#include <cuda_runtime.h>
#include <cuda_bf16.h>
#include <cuda.h>
#include <stdint.h>

namespace {

constexpr int C          = 384;
constexpr int HW         = 384;
constexpr int NPIX       = HW * HW;
constexpr int NCOARSE    = NPIX / 4;
constexpr int NSEG       = NCOARSE / 16;
constexpr int NJOBS      = 36;

constexpr int NSLOTS     = 10;
constexpr int MAXPAIRS   = 66;
constexpr int PF_LEAD    = 5;
constexpr int PF_LEAD0   = 17;
constexpr int PF_DECAY   = 10;
constexpr int PF_GAP     = 50;
constexpr int PF_GAP0    = 150;
constexpr int FIRST_EARLY = 0;
constexpr int W5TMA      = 0;
constexpr int PEARLY     = 0;
constexpr int COMMIT1    = 1;
constexpr int FMULI      = 1;
constexpr int EARLY      = 63;
constexpr int X_SAME     = 0;
constexpr int EF_FROM    = 0;
constexpr int EF_TO      = 0;
constexpr int EF_TAIL    = 27;
constexpr int ST_NFROM   = 99;
constexpr int GOV_POS    = 2;
constexpr int GOV_INC    = 0;
constexpr int GOV_QOFF   = 0;
constexpr int PF_RATE    = 2;
constexpr int PF_SKIP0   = 0;
constexpr int PF_SKIP1   = 3;
constexpr int PF_FIRST   = 7;
constexpr int HOLD       = 0;
constexpr int JOBPRIO    = 1;
constexpr int WL0        = 2;
constexpr int WL1        = 3;
constexpr int WL2        = 6;
constexpr int WL3        = 6;
constexpr int WL4        = 8;
constexpr int WL5        = 8;
constexpr int W5MODE     = 2;
constexpr int W5N        = 32;
constexpr int W5T        = 4;
constexpr int W5MASK     = 9;
constexpr int W5FROM     = 6;
constexpr int GOV_START  = 14;
constexpr int GOV_SLACK  = 0;

constexpr int SLOT_BYTES  = 8192;
constexpr int WOUT_SLICE  = 320 * 128;
constexpr int OFF_WOUT    = 0;
constexpr int OFF_RING    = 3 * WOUT_SLICE;
constexpr int OFF_STAGE   = OFF_RING + NSLOTS * SLOT_BYTES;
constexpr int OFF_BAR     = OFF_STAGE + 3 * 8192;
constexpr int OFF_FULL    = OFF_BAR;
constexpr int OFF_EMPTY   = OFF_FULL + 8 * NSLOTS;
constexpr int OFF_WBAR    = OFF_EMPTY + 8 * NSLOTS;
constexpr int OFF_JB2     = OFF_WBAR + 24;
constexpr int OFF_PACE    = OFF_JB2 + 8;
constexpr int SMEM_BYTES  = OFF_PACE + 8;
static_assert(SMEM_BYTES <= 232448, "smem");
static_assert(NSLOTS >= 10, "the first tile (nine ring items) is requested in the prologue");

constexpr int NTHREADS = 512;
constexpr uint64_t POLICY_EVICT_FIRST  = 0x12F0000000000000ull;
constexpr uint64_t POLICY_EVICT_NORMAL = 0x1000000000000000ull;

struct Scratch {
    uint4    wfrag[2 * 6 * 24 * 128];
    unsigned epoch;
    unsigned pad0[31];
    unsigned prog;
    unsigned pad1[31];
    unsigned done;
};
__device__ Scratch g_scratch;

#define TSTAMP(role, idx) do {} while (0)
#define TDUMP(role) do {} while (0)
#define LSTAMP(kind, n) do {} while (0)
__device__ __forceinline__ uint32_t smem_u32(const void* p) { return (uint32_t)__cvta_generic_to_shared(p); }

__device__ __forceinline__ void mbar_init(uint32_t bar, uint32_t cnt) {
    asm volatile("mbarrier.init.shared::cta.b64 [%0], %1;" ::"r"(bar), "r"(cnt) : "memory");
}
__device__ __forceinline__ void mbar_expect_tx(uint32_t bar, uint32_t bytes) {
    asm volatile("mbarrier.arrive.expect_tx.shared::cta.b64 _, [%0], %1;" ::"r"(bar), "r"(bytes) : "memory");
}
__device__ __forceinline__ void mbar_wait_bounded(uint32_t bar, uint32_t parity) {
    asm volatile(
        "{\n"
        ".reg .pred p;\n"
        ".reg .u32 n;\n"
        "mbarrier.try_wait.parity.shared::cta.b64 p, [%0], %1;\n"
        "@p bra DONE_%=;\n"
        "mov.u32 n, 0;\n"
        "WAIT_%=:\n"
        "mbarrier.try_wait.parity.shared::cta.b64 p, [%0], %1;\n"
        "@p bra DONE_%=;\n"
        "add.u32 n, n, 1;\n"
        "setp.lt.u32 p, n, 4000000;\n"
        "@p bra WAIT_%=;\n"
        "trap;\n"
        "DONE_%=:\n"
        "}\n" ::"r"(bar), "r"(parity) : "memory");
}
__device__ __forceinline__ void mbar_wait(uint32_t bar, uint32_t parity) {
    asm volatile(
        "{\n"
        ".reg .pred p;\n"
        "WAIT_%=:\n"
        "mbarrier.try_wait.parity.shared::cta.b64 p, [%0], %1;\n"
        "@!p bra WAIT_%=;\n"
        "}\n" ::"r"(bar), "r"(parity) : "memory");
}
__device__ __forceinline__ bool mbar_try(uint32_t bar, uint32_t parity) {
    uint32_t r;
    asm volatile("{\n.reg .pred p;\nmbarrier.test_wait.parity.shared::cta.b64 p, [%1], %2;\nselp.u32 %0, 1, 0, p;\n}\n"
                 : "=r"(r) : "r"(bar), "r"(parity) : "memory");
    return r != 0;
}
__device__ __forceinline__ void mbar_arrive_cluster(uint32_t cluster_addr) {
    asm volatile("mbarrier.arrive.shared::cluster.b64 _, [%0];" ::"r"(cluster_addr) : "memory");
}
__device__ __forceinline__ uint32_t mapa(uint32_t addr, uint32_t rank) {
    uint32_t r;
    asm("mapa.shared::cluster.u32 %0, %1, %2;" : "=r"(r) : "r"(addr), "r"(rank));
    return r;
}
__device__ __forceinline__ void named_bar(int wg) {
    asm volatile("bar.sync %0, 128;" ::"r"(wg + 1) : "memory");
}

__device__ __forceinline__ void tma_load_2d(uint32_t dst, const CUtensorMap* tm, int c0, int c1, uint32_t bar) {
    asm volatile("cp.async.bulk.tensor.2d.shared::cluster.global.mbarrier::complete_tx::bytes [%0], [%1, {%2, %3}], [%4];"
                 ::"r"(dst), "l"(tm), "r"(c0), "r"(c1), "r"(bar) : "memory");
}
__device__ __forceinline__ void tma_load_3d(uint32_t dst, const CUtensorMap* tm, int c0, int c1, int c2, uint32_t bar) {
    asm volatile("cp.async.bulk.tensor.3d.shared::cluster.global.mbarrier::complete_tx::bytes [%0], [%1, {%2, %3, %4}], [%5];"
                 ::"r"(dst), "l"(tm), "r"(c0), "r"(c1), "r"(c2), "r"(bar) : "memory");
}
__device__ __forceinline__ void tma_load_5d(uint32_t dst, const CUtensorMap* tm, int c0, int c3, int c4, uint32_t bar) {
    asm volatile("cp.async.bulk.tensor.5d.shared::cluster.global.mbarrier::complete_tx::bytes [%0], [%1, {%2, 0, 0, %3, %4}], [%5];"
                 ::"r"(dst), "l"(tm), "r"(c0), "r"(c3), "r"(c4), "r"(bar) : "memory");
}
__device__ __forceinline__ void tma_load_2d_mc(uint32_t dst, const CUtensorMap* tm, int c0, int c1, uint32_t bar, uint64_t pol) {
    asm volatile("cp.async.bulk.tensor.2d.shared::cluster.global.mbarrier::complete_tx::bytes.multicast::cluster.L2::cache_hint"
                 " [%0], [%1, {%2, %3}], [%4], %5, %6;"
                 ::"r"(dst), "l"(tm), "r"(c0), "r"(c1), "r"(bar), "h"((uint16_t)3), "l"(pol) : "memory");
}
__device__ __forceinline__ void tma_load_5d_mc(uint32_t dst, const CUtensorMap* tm, int c0, int c3, int c4, uint32_t bar, uint64_t pol) {
    asm volatile("cp.async.bulk.tensor.5d.shared::cluster.global.mbarrier::complete_tx::bytes.multicast::cluster.L2::cache_hint"
                 " [%0], [%1, {%2, 0, 0, %3, %4}], [%5], %6, %7;"
                 ::"r"(dst), "l"(tm), "r"(c0), "r"(c3), "r"(c4), "r"(bar), "h"((uint16_t)3), "l"(pol) : "memory");
}
__device__ __forceinline__ void tma_store_2d(const CUtensorMap* tm, int c0, int c1, uint32_t src, uint64_t pol) {
    asm volatile("cp.async.bulk.tensor.2d.global.shared::cta.bulk_group.L2::cache_hint [%0, {%1, %2}], [%3], %4;"
                 ::"l"(tm), "r"(c0), "r"(c1), "r"(src), "l"(pol) : "memory");
}
__device__ __forceinline__ void prefetch_tmap(const CUtensorMap* tm) {
    asm volatile("prefetch.tensormap [%0];" ::"l"(tm) : "memory");
}

__device__ __forceinline__ void wg_fence()  { asm volatile("wgmma.fence.sync.aligned;" ::: "memory"); }
__device__ __forceinline__ void wg_commit() { asm volatile("wgmma.commit_group.sync.aligned;" ::: "memory"); }
template <int N> __device__ __forceinline__ void wg_wait() { asm volatile("wgmma.wait_group.sync.aligned %0;" ::"n"(N) : "memory"); }

#define ACC16(a)                                                                                              \
    "+f"(a[0]), "+f"(a[1]), "+f"(a[2]), "+f"(a[3]), "+f"(a[4]), "+f"(a[5]), "+f"(a[6]), "+f"(a[7]),           \
    "+f"(a[8]), "+f"(a[9]), "+f"(a[10]), "+f"(a[11]), "+f"(a[12]), "+f"(a[13]), "+f"(a[14]), "+f"(a[15])
#define ACC32(a)                                                                                              \
    ACC16(a),                                                                                                 \
    "+f"(a[16]), "+f"(a[17]), "+f"(a[18]), "+f"(a[19]), "+f"(a[20]), "+f"(a[21]), "+f"(a[22]), "+f"(a[23]),   \
    "+f"(a[24]), "+f"(a[25]), "+f"(a[26]), "+f"(a[27]), "+f"(a[28]), "+f"(a[29]), "+f"(a[30]), "+f"(a[31])
#define ACC16_STR "{%0, %1, %2, %3, %4, %5, %6, %7, %8, %9, %10, %11, %12, %13, %14, %15}"
#define ACC32_STR                                                                                             \
    "{%0, %1, %2, %3, %4, %5, %6, %7, %8, %9, %10, %11, %12, %13, %14, %15, "                                 \
    "%16, %17, %18, %19, %20, %21, %22, %23, %24, %25, %26, %27, %28, %29, %30, %31}"

template <int BOFF>
__device__ __forceinline__ void wgmma_rs(float (&d)[32], uint32_t a0, uint32_t a1, uint32_t a2, uint32_t a3, uint32_t db_lo) {
    asm volatile("{\n.reg .b64 db;\n.reg .b32 lo;\n"
                 "add.u32 lo, %36, %37;\nmov.b64 db, {lo, 0x40000040};\n"
                 "wgmma.mma_async.sync.aligned.m64n64k16.f32.bf16.bf16 " ACC32_STR
                 ", {%32, %33, %34, %35}, db, 1, -1, 1, 0;\n}"
                 : ACC32(d) : "r"(a0), "r"(a1), "r"(a2), "r"(a3), "r"(db_lo), "n"(BOFF));
}
template <int ACCUM, int AOFF, int BOFF>
__device__ __forceinline__ void wgmma_ss(float (&d)[32], uint32_t da_lo, uint32_t db_lo) {
    asm volatile("{\n.reg .b64 da, db;\n.reg .b32 lo;\n"
                 "add.u32 lo, %32, %35;\nmov.b64 da, {lo, 0x40000040};\n"
                 "add.u32 lo, %33, %36;\nmov.b64 db, {lo, 0x40000040};\n"
                 "wgmma.mma_async.sync.aligned.m64n64k16.f32.bf16.bf16 " ACC32_STR
                 ", da, db, %34, 1, 1, 1, 0;\n}"
                 : ACC32(d) : "r"(da_lo), "r"(db_lo), "n"(ACCUM), "n"(AOFF), "n"(BOFF));
}
template <int ACCUM, int AOFF, int BOFF>
__device__ __forceinline__ void wgmma_ss32(float (&d)[16], uint32_t da_lo, uint32_t db_lo) {
    asm volatile("{\n.reg .b64 da, db;\n.reg .b32 lo;\n"
                 "add.u32 lo, %16, %19;\nmov.b64 da, {lo, 0x40000040};\n"
                 "add.u32 lo, %17, %20;\nmov.b64 db, {lo, 0x40000040};\n"
                 "wgmma.mma_async.sync.aligned.m64n32k16.f32.bf16.bf16 " ACC16_STR
                 ", da, db, %18, 1, 1, 1, 0;\n}"
                 : ACC16(d) : "r"(da_lo), "r"(db_lo), "n"(ACCUM), "n"(AOFF), "n"(BOFF));
}
__device__ __forceinline__ uint32_t desc_lo(uint32_t addr) { return ((addr & 0x3FFFFu) >> 4) | (1u << 16); }
__device__ __forceinline__ uint32_t pack_bf16(float lo, float hi) {
    uint32_t r;
    asm("cvt.rn.bf16x2.f32 %0, %1, %2;" : "=r"(r) : "f"(hi), "f"(lo));
    return r;
}
__device__ __forceinline__ uint32_t pack_neg(float lo, float hi) {
    const uint32_t v = pack_bf16(lo, hi) ^ 0x80008000u;
    return v == 0u ? 0x80008000u : v;
}
__device__ __forceinline__ float dup(float x, float one) {
    float r;
    asm volatile("mul.f32 %0, %1, %2;" : "=f"(r) : "f"(x), "f"(one));
    return r;
}
__device__ __forceinline__ void stsm_x4_t(uint32_t addr, uint32_t r0, uint32_t r1, uint32_t r2, uint32_t r3) {
    asm volatile("stmatrix.sync.aligned.m8n8.x4.trans.shared.b16 [%0], {%1, %2, %3, %4};"
                 ::"r"(addr), "r"(r0), "r"(r1), "r"(r2), "r"(r3) : "memory");
}

struct Ring {
    uint32_t so;
    uint32_t ph;
    __device__ __forceinline__ void advance() {
        so += 8;
        if (so == NSLOTS * 8) { so = 0; ph ^= 1; }
    }
    __device__ __forceinline__ uint32_t prev() const { return so == 0 ? (NSLOTS - 1) * 8 : so - 8; }
    __device__ __forceinline__ uint32_t back(uint32_t k) const { return so >= k * 8 ? so - k * 8 : so + (NSLOTS - k) * 8; }
};

struct Ctx {
    uint32_t sbase;
    uint32_t db0;
    uint32_t empty_tgt;
    bool     signal;
};

template <int KC, bool RS>
__device__ __forceinline__ void chunk(float (&acc)[32], const uint32_t (&W)[96], uint32_t da0, const Ctx& cx, Ring& rg, bool& ready) {
    if (!ready) mbar_wait(cx.sbase + OFF_FULL + rg.so, rg.ph);
    const uint32_t db = cx.db0 + rg.so * 64;
    const uint32_t prev = rg.prev();
    rg.advance();
    ready = ((EARLY >> KC) & 1) ? mbar_try(cx.sbase + OFF_FULL + rg.so, rg.ph) : false;
    wg_fence();
    if (RS) {
        wgmma_rs<0>(acc, W[KC * 16 + 0],  W[KC * 16 + 1],  W[KC * 16 + 2],  W[KC * 16 + 3],  db);
        wgmma_rs<2>(acc, W[KC * 16 + 4],  W[KC * 16 + 5],  W[KC * 16 + 6],  W[KC * 16 + 7],  db);
        wgmma_rs<4>(acc, W[KC * 16 + 8],  W[KC * 16 + 9],  W[KC * 16 + 10], W[KC * 16 + 11], db);
        wgmma_rs<6>(acc, W[KC * 16 + 12], W[KC * 16 + 13], W[KC * 16 + 14], W[KC * 16 + 15], db);
    } else {
        wgmma_ss<(KC > 0), (KC * 4 + 0) * 128, 0>(acc, da0, db);
        wgmma_ss<1,        (KC * 4 + 1) * 128, 2>(acc, da0, db);
        wgmma_ss<1,        (KC * 4 + 2) * 128, 4>(acc, da0, db);
        wgmma_ss<1,        (KC * 4 + 3) * 128, 6>(acc, da0, db);
    }
    wg_commit();
    if (KC > 0) {
        wg_wait<1>();
        if (cx.signal) mbar_arrive_cluster(cx.empty_tgt + prev);
    }
}

__device__ __forceinline__ void chunk_q5(float (&acc)[32], int wg, const Ctx& cx, Ring& rg, bool& ready) {
    Ring r = rg;
    const uint32_t db = cx.db0 + r.so * 64;
    uint32_t da = 0;
    bool ok = ((EARLY >> 4) & 1) ? ready : mbar_try(cx.sbase + OFF_FULL + r.so, r.ph);
#pragma unroll
    for (int g = 0; g < 3; g++) {
        r.advance();
        ok = mbar_try(cx.sbase + OFF_FULL + r.so, r.ph) && ok;
        if (g == wg) da = cx.db0 + r.so * 64;
    }
    if (!ok) {
        Ring t = rg;
#pragma unroll 1
        for (int g = 0; g < 4; g++) {
            mbar_wait(cx.sbase + OFF_FULL + t.so, t.ph);
            t.advance();
        }
    }
    r.advance();
    ready = ((EARLY >> 5) & 1) ? mbar_try(cx.sbase + OFF_FULL + r.so, r.ph) : false;
    wg_fence();
    wgmma_ss<1, 0 * 128, 0>(acc, da, db);
    wgmma_ss<1, 1 * 128, 2>(acc, da, db);
    wgmma_ss<1, 2 * 128, 4>(acc, da, db);
    wgmma_ss<1, 3 * 128, 6>(acc, da, db);
    wg_commit();
    wg_wait<1>();
    if (cx.signal) mbar_arrive_cluster(cx.empty_tgt + rg.prev());
    rg = r;
}
__device__ __forceinline__ void finish_q(const Ctx& cx, const Ring& rg) {
    wg_wait<0>();
    if (cx.signal) {
        mbar_arrive_cluster(cx.empty_tgt + rg.back(4));
        mbar_arrive_cluster(cx.empty_tgt + rg.back(3));
        mbar_arrive_cluster(cx.empty_tgt + rg.back(2));
        mbar_arrive_cluster(cx.empty_tgt + rg.back(1));
    }
}

__global__ void __cluster_dims__(2, 1, 1) __launch_bounds__(NTHREADS, 1)
fpn_kernel(Scratch* scr, const __nv_bfloat16* __restrict__ wo_ptr,
           const __nv_bfloat16* __restrict__ c_ptr, const __nv_bfloat16* __restrict__ p_ptr, const int maxfine, const float one,
           const __grid_constant__ CUtensorMap tm_w64, const __grid_constant__ CUtensorMap tm_wl3,
           const __grid_constant__ CUtensorMap tm_p8, const __grid_constant__ CUtensorMap tm_c,
           const __grid_constant__ CUtensorMap tm_p, const __grid_constant__ CUtensorMap tm_out)
{
    extern __shared__ __align__(1024) uint8_t smem[];
    const uint32_t sbase = smem_u32(smem);
    const int tid   = threadIdx.x;
    const int warp  = __shfl_sync(0xffffffffu, tid >> 5, 0);
    const int lane  = tid & 31;
    const int rank  = blockIdx.x & 1;
    const int pair  = blockIdx.x >> 1;
    const int npair = gridDim.x >> 1;

    const int nfine = maxfine - ((maxfine - 1) * npair + pair >= NSEG);
    auto seg_row = [](int g) { const int y = g / 12; return y * (2 * HW) + (g - y * 12) * 32; };

    if (tid == 480) {
        prefetch_tmap(&tm_w64); prefetch_tmap(&tm_wl3); prefetch_tmap(&tm_p8);
        prefetch_tmap(&tm_c); prefetch_tmap(&tm_p); prefetch_tmap(&tm_out);
    }
    auto first_loads = [&]() {
        const int g0 = pair % 3;
#pragma unroll 1
        for (int s = 0; s < 3; s++) {
            const uint32_t bar = sbase + OFF_FULL + s * 8;
            const uint32_t dst = sbase + OFF_WOUT + g0 * WOUT_SLICE + s * 16384;
            mbar_expect_tx(bar, pair < NJOBS ? 3 * SLOT_BYTES : 2 * SLOT_BYTES);
            tma_load_2d(dst, &tm_w64, rank * 192 + g0 * 64, s * 128, bar);
            if (pair < NJOBS) tma_load_3d(sbase + OFF_RING + s * SLOT_BYTES, &tm_wl3, 0, (pair / 3) * 32, 2 * s, bar);
            tma_load_2d(s < 2 ? dst + 8192 : sbase + OFF_STAGE + g0 * 8192, &tm_w64, rank * 192 + g0 * 64, s * 128 + 64, bar);
        }
    };
    if (tid == 384) {
        for (int s = 0; s < 3; s++) mbar_init(sbase + OFF_FULL + s * 8, 1);
        asm volatile("fence.mbarrier_init.release.cluster;" ::: "memory");
        asm volatile("fence.proxy.async.shared::cta;" ::: "memory");
        if (FIRST_EARLY) { TSTAMP(3, 5); first_loads(); }
    }
    if (warp == 13) {
        if (lane == 0) {
            for (int s = 0; s < NSLOTS; s++) {
                if (s >= 3) mbar_init(sbase + OFF_FULL + s * 8, 1);
                mbar_init(sbase + OFF_EMPTY + s * 8, 6);
            }
            for (int g = 0; g < 3; g++) mbar_init(sbase + OFF_WBAR + g * 8, 1);
            mbar_init(sbase + OFF_JB2, 1);
            asm volatile("st.volatile.shared.u32 [%0], %1;" ::"r"(sbase + OFF_PACE), "r"(6) : "memory");
            asm volatile("fence.mbarrier_init.release.cluster;" ::: "memory");
            asm volatile("fence.proxy.async.shared::cta;" ::: "memory");
        }
        __syncwarp();
        asm volatile("bar.arrive 5, 448;" ::: "memory");
        if (lane == 0) TSTAMP(3, 4);
    }
    __syncwarp();
    asm volatile("barrier.cluster.arrive.relaxed.aligned;" ::: "memory");
    if (warp >= 12) {
        asm volatile("setmaxnreg.dec.sync.aligned.u32 32;");
        if (PEARLY && tid == 416) {
            if (PEARLY > 1) __nanosleep(PEARLY);
#pragma unroll 1
            for (int kc = 0; kc < 6; kc++) {
                const uint32_t bar = sbase + OFF_FULL + (3 + kc) * 8;
                mbar_expect_tx(bar, 3 * SLOT_BYTES);
                tma_load_5d(sbase + OFF_RING + (3 + kc) * SLOT_BYTES, &tm_p8, kc * 64, pair * 2, 0, bar);
            }
        }
        if (warp == 12) {
            if (!FIRST_EARLY && lane == 0) { TSTAMP(3, 5); first_loads(); }
            __syncwarp();
            asm volatile("bar.sync 5, 448;" ::: "memory");
        }
        if (tid == 384) {
            const int g1 = (pair + 1) % 3, g2 = (pair + 2) % 3;
            if (HOLD) __nanosleep(HOLD);
            TSTAMP(3, 6);
#pragma unroll 1
            for (int kc = 0; kc < 6; kc++) {
                const uint32_t bar = sbase + OFF_FULL + (3 + kc) * 8;
                if (!PEARLY) {
                    mbar_expect_tx(bar, 3 * SLOT_BYTES);
                    tma_load_5d(sbase + OFF_RING + (3 + kc) * SLOT_BYTES, &tm_p8, kc * 64, pair * 2, 0, bar);
                }
                tma_load_2d(kc < 5 ? sbase + OFF_WOUT + g1 * WOUT_SLICE + kc * 8192 : sbase + OFF_STAGE + g1 * 8192,
                            &tm_w64, rank * 192 + g1 * 64, kc * 64, bar);
                tma_load_2d(kc < 5 ? sbase + OFF_WOUT + g2 * WOUT_SLICE + kc * 8192 : sbase + OFF_STAGE + g2 * 8192,
                            &tm_w64, rank * 192 + g2 * 64, kc * 64, bar);
            }
        }
        if (tid == 384) TSTAMP(3, 1);
        __syncwarp();
        asm volatile("barrier.cluster.wait.aligned;" ::: "memory");
        if (warp == 12) {
            if (lane == 0) {
                TSTAMP(3, 2);
                const uint32_t dst0 = sbase + OFF_RING + rank * 4096;
                uint32_t so = 9 * 8, ph = 1, step = 6;
                LSTAMP(0, 0);
                auto acquire = [&](uint32_t& bar, uint32_t& dst) {
                    bar = sbase + OFF_FULL + so;
                    dst = dst0 + so * (SLOT_BYTES / 8);
                    mbar_wait_bounded(sbase + OFF_EMPTY + so, ph);
                    mbar_expect_tx(bar, SLOT_BYTES);
                };
                auto advance = [&]() {
                    so += 8;
                    if (so == NSLOTS * 8) { so = 0; ph ^= 1; }
                    step++;
                    asm volatile("st.volatile.shared.u32 [%0], %1;" ::"r"(sbase + OFF_PACE), "r"(step) : "memory");
                };
                unsigned mytiles = 0, seen = 0;
                const unsigned maxtiles = maxfine + (maxfine - 1) / 4;
                auto govern = [&]() {
                    if (rank == 0) {
                        unsigned spins = 0;
                        while (mytiles >= GOV_START && (int)(mytiles * npair - seen) > GOV_SLACK && ++spins < 100000u)
                            asm volatile("ld.relaxed.gpu.global.u32 %0, [%1];" : "=r"(seen) : "l"(&scr->prog) : "memory");
                        mytiles++;
                        if (GOV_INC < 0) asm volatile("red.relaxed.gpu.global.add.u32 [%0], 1;" ::"l"(&scr->prog) : "memory");
                        if (GOV_POS < 0)
                        asm volatile("ld.relaxed.gpu.global.u32 %0, [%1];" : "=r"(seen) : "l"(&scr->prog) : "memory");
                    }
                };
#pragma unroll 1
                for (int j = 0; j < nfine; j++) {
                    const uint64_t pol = ((j >= EF_FROM && j < EF_TO) || j >= EF_TAIL) ? POLICY_EVICT_FIRST : POLICY_EVICT_NORMAL;
                    if ((j & 3) == 0 && j > 0) {
                        const int jc = X_SAME ? 2 * rank : (j + 2 * rank < nfine) ? j + 2 * rank : maxfine;
                        govern();
#pragma unroll
                        for (int kc = 0; kc < 6; kc++) {
                            uint32_t bar, dst;
                            acquire(bar, dst);
                            tma_load_5d_mc(dst, &tm_p, kc * 64, pair * 2, jc, bar, pol);
                            advance();
                            if (GOV_INC >= 0 && kc == GOV_INC + GOV_QOFF && rank == 0) asm volatile("red.relaxed.gpu.global.add.u32 [%0], 1;" ::"l"(&scr->prog) : "memory");
                            if (GOV_POS >= 0 && kc == GOV_POS + 3 && rank == 0)
                                asm volatile("ld.relaxed.gpu.global.u32 %0, [%1];" : "=r"(seen) : "l"(&scr->prog) : "memory");
                        }
#pragma unroll
                        for (int g = 0; g < 3; g++) {
                            uint32_t bar, dst;
                            acquire(bar, dst);
                            tma_load_2d(dst - rank * 4096, &tm_w64, rank * 192 + g * 64, 320, bar);
                            so += 8;
                            if (so == NSLOTS * 8) { so = 0; ph ^= 1; }
                            if (GOV_POS >= 0 && g == GOV_POS - 3 && rank == 0)
                                asm volatile("ld.relaxed.gpu.global.u32 %0, [%1];" : "=r"(seen) : "l"(&scr->prog) : "memory");
                        }
                    }
                    const int row = seg_row((X_SAME ? 0 : j) * npair + pair) + rank * HW;
                    govern();
#pragma unroll
                    for (int kc = 0; kc < 6; kc++) {
                        uint32_t bar, dst;
                        acquire(bar, dst);
                        tma_load_2d_mc(dst, &tm_c, kc * 64, row, bar, pol);
                        advance();
                        if (kc == GOV_INC && rank == 0) asm volatile("red.relaxed.gpu.global.add.u32 [%0], 1;" ::"l"(&scr->prog) : "memory");
                        if (kc == GOV_POS && rank == 0)
                            asm volatile("ld.relaxed.gpu.global.u32 %0, [%1];" : "=r"(seen) : "l"(&scr->prog) : "memory");
                    }
                }
                if (rank == 0) {
                    if (mytiles < maxtiles) asm volatile("red.relaxed.gpu.global.add.u32 [%0], %1;" ::"l"(&scr->prog), "r"(maxtiles - mytiles) : "memory");
                }
                for (int s = 0; s < NSLOTS; s++) {
                    mbar_wait_bounded(sbase + OFF_EMPTY + so, ph);
                    so += 8;
                    if (so == NSLOTS * 8) { so = 0; ph ^= 1; }
                }
                TSTAMP(3, 3); TDUMP(3);
                const unsigned old = atomicAdd(&scr->done, 1u);
                if (old == gridDim.x - 1) { scr->done = 0; scr->prog = 0; scr->epoch = scr->epoch + 1; }
            }
        } else if (warp == 13) {
            const int ntiles = nfine + (nfine + 3) / 4;
            uint32_t sink = 0, pv = 0;
#pragma unroll 1
            for (int i = 1; i < (X_SAME ? 0 : ntiles); i++) {
                const int k5 = i / 5, t = i - k5 * 5;
                const char *b0, *b1;
                if (t == 0) {
                    const int g = min((4 * k5 + 2 * rank) * npair + pair, NSEG - 1);
                    b0 = (const char*)p_ptr + (size_t)g * (16 * C * 2);
                    b1 = (const char*)p_ptr + (size_t)min(g + npair, NSEG - 1) * (16 * C * 2);
                } else {
                    b0 = (const char*)c_ptr + (size_t)(seg_row((4 * k5 + t - 1) * npair + pair) + rank * HW) * (C * 2);
                    b1 = b0 + 16 * C * 2;
                }
                const int extra = PF_LEAD0 - PF_LEAD - (i > PF_DECAY ? (i - PF_DECAY) * PF_RATE / 2 : 0);
                int need = 6 * i - PF_LEAD - (extra > 0 ? extra : 0);
                if (need < PF_FIRST) need = PF_FIRST;
                unsigned spins = 0;
                while (true) {
                    uint32_t v;
                    asm volatile("ld.volatile.shared.u32 %0, [%1];" : "=r"(v) : "r"(sbase + OFF_PACE) : "memory");
                    if ((int)v >= need || ++spins > 4000000u) break;
                    __nanosleep(20);
                }
                if (lane == 0) LSTAMP(2, i);
                if (i < PF_SKIP0 || i >= PF_SKIP1)
#pragma unroll
                for (int k = 0; k < 6; k++) {
                    asm volatile("prefetch.global.L2 [%0];" ::"l"((k < 3 ? b0 : b1) + lane * 128 + (k % 3) * 4096) : "memory");
                    __nanosleep(need == PF_FIRST ? PF_GAP0 : PF_GAP);
                }
                if (W5MODE == 0) {
                if (t == 0) {
#pragma unroll
                    for (int k = 0; k < 6; k++) {
                        const int idx = k * 32 + lane;
                        asm volatile("prefetch.global.L2 [%0];" ::"l"((const char*)wo_ptr + (320 + idx / 3) * (C * 2) + rank * 384 + (idx % 3) * 128) : "memory");
                    }
                }
                } else if (W5MODE == 2 || W5MODE == 3) {
                    const int idx = ((pair + i * 5) % (192 / W5N)) * W5N + lane;
                    if (lane < W5N && ((W5MASK >> t) & 1) && i >= W5FROM) {
                        sink ^= pv;
                        asm volatile("ld.global.cg.u32 %0, [%1];" : "=r"(pv) : "l"((const char*)wo_ptr + (320 + idx / 3) * (C * 2) + rank * 384 + (idx % 3) * 128) : "memory");
                    }
                } else if (W5MODE == 4) {
                    const int idx = (pair % 6) * 32 + lane;
                    if (t == W5T)
                        asm volatile("prefetch.global.L2 [%0];" ::"l"((const char*)wo_ptr + (320 + idx / 3) * (C * 2) + rank * 384 + (idx % 3) * 128) : "memory");
                }
            }
            asm volatile("st.volatile.shared.u32 [%0], %1;" ::"r"(sbase + OFF_PACE + 4), "r"(sink ^ pv) : "memory");
        }
    } else {
        uint32_t par;
        asm volatile("ld.relaxed.gpu.global.u32 %0, [%1];" : "=r"(par) : "l"(&scr->epoch) : "memory");
        asm volatile("setmaxnreg.inc.sync.aligned.u32 160;");
        asm volatile("bar.sync 5, 448;" ::: "memory");
        const int wg   = warp >> 2;
        const int wtid = tid & 127;
        Ctx cx;
        cx.sbase     = sbase;
        cx.db0       = desc_lo(sbase + OFF_RING);
        cx.empty_tgt = mapa(sbase + OFF_EMPTY, warp & 1);
        cx.signal    = (lane == 0) && ((warp & 3) < 2);
        const uint32_t da0 = desc_lo(sbase + OFF_WOUT + wg * WOUT_SLICE);
        const int cb = rank * 3 + wg;

        float    acc[32];
        uint32_t qp[16];
        uint32_t W[96];
        Ring rg{0u, 0u};

        const uint32_t da5 = desc_lo(sbase + OFF_STAGE + wg * 8192) - 20 * 128;

        if (wtid == 0) TSTAMP(wg, 0);
        {
            uint32_t jph = 0;
            for (int job = pair; job < NJOBS; job += npair) {
                if (job % 3 == wg) {
                    if (job != pair) {
                        named_bar(wg);
                        if (wtid == 0) {
                            mbar_expect_tx(sbase + OFF_JB2, 6 * 4096);
                            for (int s = 0; s < 3; s++)
                                tma_load_3d(sbase + OFF_RING + s * SLOT_BYTES, &tm_wl3, 0, (job / 3) * 32, 2 * s, sbase + OFF_JB2);
                        }
                        for (int kc = 0; kc < 6; kc++) mbar_wait(sbase + OFF_FULL + (3 + kc) * 8, 0);
                        mbar_wait(sbase + OFF_JB2, jph);
                    }
                    float ja[16];
#define JOBK(k) wgmma_ss32<((k) > 0), (k) * 128, ((k) >> 2) * 256 + ((k) & 3) * 2>(ja, (k) < 20 ? da0 : da5, cx.db0);
                    mbar_wait(sbase + OFF_FULL, 0);
                    if (wtid == 0) TSTAMP(wg, 46);
                    wg_fence();
                    JOBK(0)  JOBK(1)  JOBK(2)  JOBK(3)  JOBK(4)  JOBK(5)  JOBK(6)  JOBK(7)
                    wg_commit();
                    mbar_wait(sbase + OFF_FULL + 8, 0);
                    wg_fence();
                    JOBK(8)  JOBK(9)  JOBK(10) JOBK(11) JOBK(12) JOBK(13) JOBK(14) JOBK(15)
                    wg_commit();
                    mbar_wait(sbase + OFF_FULL + 16, 0);
                    if (wtid == 0) TSTAMP(wg, 47);
                    wg_fence();
                    JOBK(16) JOBK(17) JOBK(18) JOBK(19) JOBK(20) JOBK(21) JOBK(22) JOBK(23)
#undef JOBK
                    wg_commit();
                    wg_wait<0>();
                    if (wtid == 0) TSTAMP(wg, 48);
                    const int fidx = (cb * 24 + (job / 3) * 2) * 128 + wtid;
                    uint4* dst = scr->wfrag + (par & 1) * (6 * 24 * 128) + fidx;
#pragma unroll
                    for (int i = 0; i < 2; i++) {
                        asm volatile("st.relaxed.gpu.global.v4.u32 [%0], {%1, %2, %3, %4};" ::"l"(dst + i * 128),
                                     "r"(pack_neg(ja[8 * i + 0], ja[8 * i + 1])), "r"(pack_neg(ja[8 * i + 2], ja[8 * i + 3])),
                                     "r"(pack_neg(ja[8 * i + 4], ja[8 * i + 5])), "r"(pack_neg(ja[8 * i + 6], ja[8 * i + 7])) : "memory");
                    }
                }
                if (job % 3 == wg && wtid == 0) TSTAMP(wg, 49);
                if (job + npair < NJOBS) asm volatile("bar.sync 4, 384;" ::: "memory");
                if (job != pair) jph ^= 1;
            }
        }

        par &= 1;
        if (JOBPRIO && pair < NJOBS) asm volatile("bar.sync 6, 384;" ::: "memory");
        if (wtid == 0) TSTAMP(wg, 1);
        asm volatile("barrier.cluster.wait.aligned;" ::: "memory");

        mbar_wait(sbase + OFF_FULL, 0);
        mbar_wait(sbase + OFF_FULL + 8, 0);
        mbar_wait(sbase + OFF_FULL + 16, 0);
        if (cx.signal) {
            mbar_arrive_cluster(cx.empty_tgt);
            mbar_arrive_cluster(cx.empty_tgt + 8);
            mbar_arrive_cluster(cx.empty_tgt + 16);
        }
        rg.so = 3 * 8;
        bool ready = false;

        const uint4* wsrc = scr->wfrag + (par * 6 + cb) * (24 * 128) + wtid;
        auto load_w = [&](int kc) {
#pragma unroll
            for (int s = 4 * kc; s < 4 * kc + 4; s++) {
                asm volatile("ld.relaxed.gpu.global.v4.u32 {%0, %1, %2, %3}, [%4];"
                             : "=r"(W[4 * s]), "=r"(W[4 * s + 1]), "=r"(W[4 * s + 2]), "=r"(W[4 * s + 3])
                             : "l"(wsrc + s * 128) : "memory");
            }
        };
        auto load_at = [&](int pos) {
            if (WL0 == pos) load_w(0);
            if (WL1 == pos) load_w(1);
            if (WL2 == pos) load_w(2);
            if (WL3 == pos) load_w(3);
            if (WL4 == pos) load_w(4);
            if (WL5 == pos) {
                if (!W5TMA) load_w(5);
                else {
                    mbar_wait(sbase + OFF_WBAR + wg * 8, 0);
#pragma unroll
                    for (int s = 0; s < 4; s++) {
                        uint32_t* w = W + 80 + 4 * s;
                        asm volatile("ld.shared.v4.u32 {%0, %1, %2, %3}, [%4];" : "=r"(w[0]), "=r"(w[1]), "=r"(w[2]), "=r"(w[3])
                                     : "r"(sbase + OFF_STAGE + wg * 8192 + wtid * 16 + s * 2048) : "memory");
                    }
                }
            }
        };
        auto check_w = [&](int kc) {
            uint32_t* w = W + 16 * kc;
            asm volatile(
                "{\n.reg .pred p;\n.reg .u32 m, n;\n"
                "mov.u32 n, 0;\n"
                "CHK_%=:\n"
                "min.u32 m, %0, %1;\n min.u32 m, m, %2;\n min.u32 m, m, %3;\n min.u32 m, m, %4;\n min.u32 m, m, %5;\n"
                "min.u32 m, m, %6;\n min.u32 m, m, %7;\n min.u32 m, m, %8;\n min.u32 m, m, %9;\n min.u32 m, m, %10;\n"
                "min.u32 m, m, %11;\n min.u32 m, m, %12;\n min.u32 m, m, %13;\n min.u32 m, m, %14;\n min.u32 m, m, %15;\n"
                "setp.ne.u32 p, m, 0;\n"
                "vote.sync.all.pred p, p, 0xffffffff;\n"
                "@p bra.uni OK_%=;\n"
                "add.u32 n, n, 1;\n"
                "setp.gt.u32 p, n, 5000000;\n"
                "@p bra.uni OK_%=;\n"
                "ld.relaxed.gpu.global.v4.u32 {%0, %1, %2, %3}, [%16];\n"
                "ld.relaxed.gpu.global.v4.u32 {%4, %5, %6, %7}, [%16 + 2048];\n"
                "ld.relaxed.gpu.global.v4.u32 {%8, %9, %10, %11}, [%16 + 4096];\n"
                "ld.relaxed.gpu.global.v4.u32 {%12, %13, %14, %15}, [%16 + 6144];\n"
                "bra.uni CHK_%=;\n"
                "OK_%=:\n}"
                : "+r"(w[0]), "+r"(w[1]), "+r"(w[2]), "+r"(w[3]), "+r"(w[4]), "+r"(w[5]), "+r"(w[6]), "+r"(w[7]),
                  "+r"(w[8]), "+r"(w[9]), "+r"(w[10]), "+r"(w[11]), "+r"(w[12]), "+r"(w[13]), "+r"(w[14]), "+r"(w[15])
                : "l"(wsrc + kc * 512) : "memory");
        };
        {
            chunk<0, false>(acc, W, da0, cx, rg, ready);
            if (wtid == 0) TSTAMP(wg, 50);
            load_at(0);
            chunk<1, false>(acc, W, da0, cx, rg, ready);
            load_at(1);
            chunk<2, false>(acc, W, da0, cx, rg, ready);
            if (wtid == 0) TSTAMP(wg, 51);
            load_at(2);
            chunk<3, false>(acc, W, da0, cx, rg, ready);
            load_at(3);
            chunk<4, false>(acc, W, da0, cx, rg, ready);
            if (wtid == 0) TSTAMP(wg, 52);
            load_at(4);
            chunk<5, false>(acc, W, da5, cx, rg, ready);
            load_at(5);
            wg_wait<0>();
            if (cx.signal) mbar_arrive_cluster(cx.empty_tgt + rg.prev());
            if (W5TMA && wtid == 64) {
                mbar_expect_tx(sbase + OFF_WBAR + wg * 8, 8192);
                asm volatile("cp.async.bulk.shared::cluster.global.mbarrier::complete_tx::bytes [%0], [%1], 8192, [%2];"
                             ::"r"(sbase + OFF_STAGE + wg * 8192), "l"(wsrc - 64 + 20 * 128), "r"(sbase + OFF_WBAR + wg * 8) : "memory");
            }
#pragma unroll
            for (int j = 0; j < 16; j++) qp[j] = pack_bf16(acc[2 * j], acc[2 * j + 1]);
            if (wtid == 0) TSTAMP(wg, 2);
        }

        const uint32_t stage = sbase + OFF_STAGE + wg * 8192;
        const uint32_t st_addr = stage + (((lane >> 4) * 8 + (lane & 7)) << 7)
                               + (((((warp & 3) << 1) | ((lane >> 3) & 1)) ^ (lane & 7)) << 4);
        auto flush_part = [&](int row, int part) {
            if (part == 0) {
                asm volatile("fence.proxy.async.shared::cta;" ::: "memory");
                named_bar(wg);
            }
            if (wtid == 0) {
                tma_store_2d(&tm_out, cb * 64, row + (part >> 1) * HW + (part & 1) * 16, stage + part * 2048, (ST_NFROM < 99 && row >= ST_NFROM * 4224) ? POLICY_EVICT_NORMAL : POLICY_EVICT_FIRST);
                if (COMMIT1 == 0 || (COMMIT1 == 1 && part == 3)) asm volatile("cp.async.bulk.commit_group;" ::: "memory");
            }
        };

        auto init_acc = [&]() {
#pragma unroll
            for (int b = 0; b < 2; b++) {
#pragma unroll
                for (int h = 0; h < 2; h++) {
                    const uint32_t q = qp[b * 2 + h];
                    const float lo = __uint_as_float(q << 16), hi = __uint_as_float(q & 0xffff0000u);
#pragma unroll
                    for (int dy = 0; dy < 2; dy++) {
                        acc[16 * dy + 8 * b + 2 * h]         = (FMULI && dy) ? dup(lo, one) : lo;
                        acc[16 * dy + 8 * b + 2 * h + 1]     = FMULI ? dup(lo, one) : lo;
                        acc[16 * dy + 8 * b + 4 + 2 * h]     = (FMULI && dy) ? dup(hi, one) : hi;
                        acc[16 * dy + 8 * b + 4 + 2 * h + 1] = FMULI ? dup(hi, one) : hi;
                    }
                }
            }
#pragma unroll
            for (int i = 0; i < 12; i++) qp[i] = qp[i + 4];
        };
        auto stage_tile = [&]() {
            wg_wait<0>();
            if (cx.signal) mbar_arrive_cluster(cx.empty_tgt + rg.prev());
#pragma unroll
            for (int i = 0; i < 8; i += 2) {
                stsm_x4_t(st_addr + i * 1024,
                          pack_bf16(acc[4 * i + 0], acc[4 * i + 1]), pack_bf16(acc[4 * i + 2], acc[4 * i + 3]),
                          pack_bf16(acc[4 * i + 4], acc[4 * i + 5]), pack_bf16(acc[4 * i + 6], acc[4 * i + 7]));
            }
        };

        init_acc();
        check_w(0);
        if (wtid == 0) TSTAMP(wg, 3);
        chunk<0, true>(acc, W, da0, cx, rg, ready);
        load_at(6);
        check_w(1);
        chunk<1, true>(acc, W, da0, cx, rg, ready);
        load_at(7);
        check_w(2);
        chunk<2, true>(acc, W, da0, cx, rg, ready);
        load_at(8);
        check_w(3);
        chunk<3, true>(acc, W, da0, cx, rg, ready);
        load_at(9);
        check_w(4);
        chunk<4, true>(acc, W, da0, cx, rg, ready);
        check_w(5);
        if (wtid == 0) TSTAMP(wg, 4);
        chunk<5, true>(acc, W, da0, cx, rg, ready);
        int prow = seg_row(pair);
        int j = 1;
        while (true) {
            if (wtid == 0) {
                if (COMMIT1 == 2) asm volatile("cp.async.bulk.commit_group;" ::: "memory");
                asm volatile("cp.async.bulk.wait_group.read 0;" ::: "memory");
            }
            named_bar(wg);
            if (j >= nfine) break;
            const bool pend = (j & 3) != 0;
            if (!((EARLY >> 5) & 1)) ready = mbar_try(sbase + OFF_FULL + rg.so, rg.ph);
            if (pend) {
                stage_tile();
                init_acc();
                chunk<0, true>(acc, W, da0, cx, rg, ready);
                flush_part(prow, 0);
            } else {
                stage_tile();
                chunk<0, false>(acc, W, da0, cx, rg, ready);
                flush_part(prow, 0);
                chunk<1, false>(acc, W, da0, cx, rg, ready);
                chunk<2, false>(acc, W, da0, cx, rg, ready);
                flush_part(prow, 1);
                chunk<3, false>(acc, W, da0, cx, rg, ready);
                chunk<4, false>(acc, W, da0, cx, rg, ready);
                flush_part(prow, 2);
                chunk_q5(acc, wg, cx, rg, ready);
                flush_part(prow, 3);
                if (!((EARLY >> 5) & 1)) ready = mbar_try(sbase + OFF_FULL + rg.so, rg.ph);
                finish_q(cx, rg);
#pragma unroll
                for (int i = 0; i < 16; i++) qp[i] = pack_bf16(acc[2 * i], acc[2 * i + 1]);
                init_acc();
                chunk<0, true>(acc, W, da0, cx, rg, ready);
            }
            chunk<1, true>(acc, W, da0, cx, rg, ready);
            if (pend) flush_part(prow, 1);
            chunk<2, true>(acc, W, da0, cx, rg, ready);
            chunk<3, true>(acc, W, da0, cx, rg, ready);
            if (pend) flush_part(prow, 2);
            chunk<4, true>(acc, W, da0, cx, rg, ready);
            if (pend) flush_part(prow, 3);
            chunk<5, true>(acc, W, da0, cx, rg, ready);
            prow = seg_row((X_SAME ? 0 : j) * npair + pair);
            j++;
        }
        stage_tile();
#pragma unroll
        for (int part = 0; part < 4; part++) flush_part(prow, part);
        for (int job = pair; job < NJOBS; job += npair) {
            if (job % 3 == wg) {
                uint4* clr = scr->wfrag + (par ^ 1) * (6 * 24 * 128) + (cb * 24 + (job / 3) * 2) * 128 + wtid;
                clr[0]   = make_uint4(0u, 0u, 0u, 0u);
                clr[128] = make_uint4(0u, 0u, 0u, 0u);
            }
        }
        if (wtid == 0) {
            if (COMMIT1 == 2) asm volatile("cp.async.bulk.commit_group;" ::: "memory");
            asm volatile("cp.async.bulk.wait_group.read 0;" ::: "memory");
        }
        if (wtid == 0) { TSTAMP(wg, 45); TDUMP(wg); }
    }
}

typedef CUresult (*EncodeFn)(CUtensorMap*, CUtensorMapDataType, cuuint32_t, void*, const cuuint64_t*, const cuuint64_t*,
                             const cuuint32_t*, const cuuint32_t*, CUtensorMapInterleave, CUtensorMapSwizzle,
                             CUtensorMapL2promotion, CUtensorMapFloatOOBfill);

void encode(EncodeFn fn, CUtensorMap* tm, const void* ptr, int rank, const cuuint64_t* dims, const cuuint64_t* strides,
            const cuuint32_t* box) {
    const cuuint32_t es[5] = {1, 1, 1, 1, 1};
    fn(tm, CU_TENSOR_MAP_DATA_TYPE_BFLOAT16, (cuuint32_t)rank, const_cast<void*>(ptr), dims, strides, box, es,
       CU_TENSOR_MAP_INTERLEAVE_NONE, CU_TENSOR_MAP_SWIZZLE_128B, CU_TENSOR_MAP_L2_PROMOTION_NONE,
       CU_TENSOR_MAP_FLOAT_OOB_FILL_NONE);
}

}

extern "C" void kernel_launch(void* const* d_in, const int* in_sizes, int n_in, void* d_out, int out_size) {
    (void)in_sizes; (void)n_in; (void)out_size;
    const __nv_bfloat16* c_fine   = (const __nv_bfloat16*)d_in[0];
    const __nv_bfloat16* p_coarse = (const __nv_bfloat16*)d_in[1];
    const __nv_bfloat16* w_lat    = (const __nv_bfloat16*)d_in[2];
    const __nv_bfloat16* w_out    = (const __nv_bfloat16*)d_in[3];

    static EncodeFn fn = nullptr;
    static int grid = 0;
    static Scratch* scr = nullptr;
    if (!fn) {
        void* p = nullptr;
        cudaDriverEntryPointQueryResult qr;
        cudaGetDriverEntryPoint("cuTensorMapEncodeTiled", &p, cudaEnableDefault, &qr);
        fn = (EncodeFn)p;
        cudaGetSymbolAddress((void**)&scr, g_scratch);
        cudaFuncSetAttribute(fpn_kernel, cudaFuncAttributeMaxDynamicSharedMemorySize, SMEM_BYTES);
        cudaLaunchConfig_t cfg = {};
        cfg.gridDim = dim3(2); cfg.blockDim = dim3(NTHREADS); cfg.dynamicSmemBytes = SMEM_BYTES;
        cudaLaunchAttribute at[1];
        at[0].id = cudaLaunchAttributeClusterDimension;
        at[0].val.clusterDim.x = 2; at[0].val.clusterDim.y = 1; at[0].val.clusterDim.z = 1;
        cfg.attrs = at; cfg.numAttrs = 1;
        int ncl = 0;
        if (cudaOccupancyMaxActiveClusters(&ncl, fpn_kernel, &cfg) != cudaSuccess || ncl < 1) ncl = 1;
        if (ncl >= MAXPAIRS) ncl = MAXPAIRS;
        else while ((NSEG / 4) % ncl) ncl--;
        grid = 2 * ncl;
    }

    CUtensorMap tm_c, tm_p, tm_wl3, tm_out, tm_p8, tm_w64;
    {
        const cuuint64_t dims[2] = {(cuuint64_t)C, (cuuint64_t)NPIX};
        const cuuint64_t str[1]  = {(cuuint64_t)C * 2};
        const cuuint32_t box_in[2]  = {64, 32};
        const cuuint32_t box_out[2] = {64, 16};
        encode(fn, &tm_c, c_fine, 2, dims, str, box_in);
        encode(fn, &tm_out, d_out, 2, dims, str, box_out);
    }
    {
        const int np = grid / 2;
        const cuuint64_t dims[5] = {(cuuint64_t)C, 2, 4, (cuuint64_t)(2 * np), (cuuint64_t)((NSEG + np - 1) / np)};
        const cuuint64_t str[4]  = {(cuuint64_t)4 * C * 2, (cuuint64_t)C * 2, (cuuint64_t)8 * C * 2, (cuuint64_t)np * 16 * C * 2};
        const cuuint32_t box[5]  = {64, 2, 4, 2, 2};
        encode(fn, &tm_p, p_coarse, 5, dims, str, box);
        const cuuint32_t box8[5] = {64, 2, 4, 2, 4};
        encode(fn, &tm_p8, p_coarse, 5, dims, str, box8);
    }
    {
        const cuuint64_t dims[2] = {(cuuint64_t)C, (cuuint64_t)C};
        const cuuint64_t str[1]  = {(cuuint64_t)C * 2};
        const cuuint32_t box_k[2] = {64, 64};
        encode(fn, &tm_w64, w_out, 2, dims, str, box_k);
    }
    {
        const cuuint64_t dims[3] = {64, (cuuint64_t)C, 6};
        const cuuint64_t str[2]  = {(cuuint64_t)C * 2, 128};
        const cuuint32_t box[3]  = {64, 32, 2};
        encode(fn, &tm_wl3, w_lat, 3, dims, str, box);
    }
    fpn_kernel<<<grid, NTHREADS, SMEM_BYTES>>>(scr, w_out, c_fine, p_coarse, (NSEG + grid / 2 - 1) / (grid / 2), 1.0f,
                                               tm_w64, tm_wl3, tm_p8, tm_c, tm_p, tm_out);
}
```

```cpp
#include <cuda_runtime.h>
#include <cuda_bf16.h>
#include <cuda.h>
#include <stdint.h>

namespace {

constexpr int C          = 384;
constexpr int HW         = 384;
constexpr int NPIX       = HW * HW;
constexpr int NCOARSE    = NPIX / 4;
constexpr int NSEG       = NCOARSE / 16;
constexpr int NJOBS      = 36;

constexpr int NSLOTS     = 10;
constexpr int MAXPAIRS   = 64;
constexpr int PF_LEAD    = 5;
constexpr int PF_LEAD0   = 17;
constexpr int PF_DECAY   = 8;
constexpr int PF_GAP     = 50;
constexpr int PF_GAP0    = 150;
constexpr int FIRST_EARLY = 1;
constexpr int W5TMA      = 0;
constexpr int PEARLY     = 0;
constexpr int COMMIT1    = 1;
constexpr int FMULI      = 1;
constexpr int EARLY      = 63;
constexpr int X_SAME     = 0;
constexpr int EF_FROM    = 0;
constexpr int EF_TO      = 0;
constexpr int EF_TAIL    = 26;
constexpr int ST_NFROM   = 99;
constexpr int GOV_POS    = 3;
constexpr int GOV_INC    = 0;
constexpr int GOV_QOFF   = 0;
constexpr int PF_RATE    = 2;
constexpr int CLR_AT     = 20;
constexpr int SP0        = 0;
constexpr int SP1        = 2;
constexpr int SP2        = 3;
constexpr int SP3        = 4;
constexpr int SQ0        = 0;
constexpr int SQ1        = 2;
constexpr int SQ2        = 4;
constexpr int SQ3        = 5;
constexpr int PF_IB      = 0;
constexpr int PF_I0      = 4;
constexpr int PF_I1      = 4;
constexpr int PF_GAP1    = 100;
constexpr int PF_SKIP1   = 3;
constexpr int PF_FIRST   = 9;
constexpr int HOLD       = 0;
constexpr int JOBPRIO    = 1;
constexpr int WL0        = 2;
constexpr int WL1        = 3;
constexpr int WL2        = 6;
constexpr int WL3        = 6;
constexpr int WL4        = 8;
constexpr int WL5        = 8;
constexpr int W5MODE     = 2;
constexpr int W5N        = 32;
constexpr int W5T        = 4;
constexpr int W5MASK     = 9;
constexpr int W5FROM     = 6;
constexpr int GOV_START  = 18;
constexpr int GOV_SLACK  = 0;

constexpr int SLOT_BYTES  = 8192;
constexpr int WOUT_SLICE  = 320 * 128;
constexpr int OFF_WOUT    = 0;
constexpr int OFF_RING    = 3 * WOUT_SLICE;
constexpr int OFF_STAGE   = OFF_RING + NSLOTS * SLOT_BYTES;
constexpr int OFF_BAR     = OFF_STAGE + 3 * 8192;
constexpr int OFF_FULL    = OFF_BAR;
constexpr int OFF_EMPTY   = OFF_FULL + 8 * NSLOTS;
constexpr int OFF_WBAR    = OFF_EMPTY + 8 * NSLOTS;
constexpr int OFF_JB2     = OFF_WBAR + 24;
constexpr int OFF_PACE    = OFF_JB2 + 8;
constexpr int SMEM_BYTES  = OFF_PACE + 8;
static_assert(SMEM_BYTES <= 232448, "smem");
static_assert(NSLOTS >= 10, "the first tile (nine ring items) is requested in the prologue");

constexpr int NTHREADS = 512;
constexpr uint64_t POLICY_EVICT_FIRST  = 0x12F0000000000000ull;
constexpr uint64_t POLICY_EVICT_NORMAL = 0x1000000000000000ull;

struct Scratch {
    uint4    wfrag[2 * 6 * 24 * 128];
    unsigned epoch;
    unsigned pad0[31];
    unsigned prog;
};
__device__ Scratch g_scratch;

#define TSTAMP(role, idx) do {} while (0)
#define TDUMP(role) do {} while (0)
#define LSTAMP(kind, n) do {} while (0)
__device__ __forceinline__ uint32_t smem_u32(const void* p) { return (uint32_t)__cvta_generic_to_shared(p); }

__device__ __forceinline__ void mbar_init(uint32_t bar, uint32_t cnt) {
    asm volatile("mbarrier.init.shared::cta.b64 [%0], %1;" ::"r"(bar), "r"(cnt) : "memory");
}
__device__ __forceinline__ void mbar_expect_tx(uint32_t bar, uint32_t bytes) {
    asm volatile("mbarrier.arrive.expect_tx.shared::cta.b64 _, [%0], %1;" ::"r"(bar), "r"(bytes) : "memory");
}
__device__ __forceinline__ void mbar_wait_bounded(uint32_t bar, uint32_t parity) {
    asm volatile(
        "{\n"
        ".reg .pred p;\n"
        ".reg .u32 n;\n"
        "mbarrier.try_wait.parity.shared::cta.b64 p, [%0], %1;\n"
        "@p bra DONE_%=;\n"
        "mov.u32 n, 0;\n"
        "WAIT_%=:\n"
        "mbarrier.try_wait.parity.shared::cta.b64 p, [%0], %1;\n"
        "@p bra DONE_%=;\n"
        "add.u32 n, n, 1;\n"
        "setp.lt.u32 p, n, 4000000;\n"
        "@p bra WAIT_%=;\n"
        "trap;\n"
        "DONE_%=:\n"
        "}\n" ::"r"(bar), "r"(parity) : "memory");
}
__device__ __forceinline__ void mbar_wait(uint32_t bar, uint32_t parity) {
    asm volatile(
        "{\n"
        ".reg .pred p;\n"
        "WAIT_%=:\n"
        "mbarrier.try_wait.parity.shared::cta.b64 p, [%0], %1;\n"
        "@!p bra WAIT_%=;\n"
        "}\n" ::"r"(bar), "r"(parity) : "memory");
}
__device__ __forceinline__ bool mbar_try(uint32_t bar, uint32_t parity) {
    uint32_t r;
    asm volatile("{\n.reg .pred p;\nmbarrier.test_wait.parity.shared::cta.b64 p, [%1], %2;\nselp.u32 %0, 1, 0, p;\n}\n"
                 : "=r"(r) : "r"(bar), "r"(parity) : "memory");
    return r != 0;
}
__device__ __forceinline__ void mbar_arrive_cluster(uint32_t cluster_addr) {
    asm volatile("mbarrier.arrive.shared::cluster.b64 _, [%0];" ::"r"(cluster_addr) : "memory");
}
__device__ __forceinline__ uint32_t mapa(uint32_t addr, uint32_t rank) {
    uint32_t r;
    asm("mapa.shared::cluster.u32 %0, %1, %2;" : "=r"(r) : "r"(addr), "r"(rank));
    return r;
}
__device__ __forceinline__ void named_bar(int wg) {
    asm volatile("bar.sync %0, 128;" ::"r"(wg + 1) : "memory");
}

__device__ __forceinline__ void tma_load_2d(uint32_t dst, const CUtensorMap* tm, int c0, int c1, uint32_t bar) {
    asm volatile("cp.async.bulk.tensor.2d.shared::cluster.global.mbarrier::complete_tx::bytes [%0], [%1, {%2, %3}], [%4];"
                 ::"r"(dst), "l"(tm), "r"(c0), "r"(c1), "r"(bar) : "memory");
}
__device__ __forceinline__ void tma_load_3d(uint32_t dst, const CUtensorMap* tm, int c0, int c1, int c2, uint32_t bar) {
    asm volatile("cp.async.bulk.tensor.3d.shared::cluster.global.mbarrier::complete_tx::bytes [%0], [%1, {%2, %3, %4}], [%5];"
                 ::"r"(dst), "l"(tm), "r"(c0), "r"(c1), "r"(c2), "r"(bar) : "memory");
}
__device__ __forceinline__ void tma_load_5d(uint32_t dst, const CUtensorMap* tm, int c0, int c3, int c4, uint32_t bar) {
    asm volatile("cp.async.bulk.tensor.5d.shared::cluster.global.mbarrier::complete_tx::bytes [%0], [%1, {%2, 0, 0, %3, %4}], [%5];"
                 ::"r"(dst), "l"(tm), "r"(c0), "r"(c3), "r"(c4), "r"(bar) : "memory");
}
__device__ __forceinline__ void tma_load_2d_mc(uint32_t dst, const CUtensorMap* tm, int c0, int c1, uint32_t bar, uint64_t pol) {
    asm volatile("cp.async.bulk.tensor.2d.shared::cluster.global.mbarrier::complete_tx::bytes.multicast::cluster.L2::cache_hint"
                 " [%0], [%1, {%2, %3}], [%4], %5, %6;"
                 ::"r"(dst), "l"(tm), "r"(c0), "r"(c1), "r"(bar), "h"((uint16_t)3), "l"(pol) : "memory");
}
__device__ __forceinline__ void tma_load_5d_mc(uint32_t dst, const CUtensorMap* tm, int c0, int c3, int c4, uint32_t bar, uint64_t pol) {
    asm volatile("cp.async.bulk.tensor.5d.shared::cluster.global.mbarrier::complete_tx::bytes.multicast::cluster.L2::cache_hint"
                 " [%0], [%1, {%2, 0, 0, %3, %4}], [%5], %6, %7;"
                 ::"r"(dst), "l"(tm), "r"(c0), "r"(c3), "r"(c4), "r"(bar), "h"((uint16_t)3), "l"(pol) : "memory");
}
__device__ __forceinline__ void tma_store_2d(const CUtensorMap* tm, int c0, int c1, uint32_t src, uint64_t pol) {
    asm volatile("cp.async.bulk.tensor.2d.global.shared::cta.bulk_group.L2::cache_hint [%0, {%1, %2}], [%3], %4;"
                 ::"l"(tm), "r"(c0), "r"(c1), "r"(src), "l"(pol) : "memory");
}
__device__ __forceinline__ void prefetch_tmap(const CUtensorMap* tm) {
    asm volatile("prefetch.tensormap [%0];" ::"l"(tm) : "memory");
}

__device__ __forceinline__ void wg_fence()  { asm volatile("wgmma.fence.sync.aligned;" ::: "memory"); }
__device__ __forceinline__ void wg_commit() { asm volatile("wgmma.commit_group.sync.aligned;" ::: "memory"); }
template <int N> __device__ __forceinline__ void wg_wait() { asm volatile("wgmma.wait_group.sync.aligned %0;" ::"n"(N) : "memory"); }

#define ACC16(a)                                                                                              \
    "+f"(a[0]), "+f"(a[1]), "+f"(a[2]), "+f"(a[3]), "+f"(a[4]), "+f"(a[5]), "+f"(a[6]), "+f"(a[7]),           \
    "+f"(a[8]), "+f"(a[9]), "+f"(a[10]), "+f"(a[11]), "+f"(a[12]), "+f"(a[13]), "+f"(a[14]), "+f"(a[15])
#define ACC32(a)                                                                                              \
    ACC16(a),                                                                                                 \
    "+f"(a[16]), "+f"(a[17]), "+f"(a[18]), "+f"(a[19]), "+f"(a[20]), "+f"(a[21]), "+f"(a[22]), "+f"(a[23]),   \
    "+f"(a[24]), "+f"(a[25]), "+f"(a[26]), "+f"(a[27]), "+f"(a[28]), "+f"(a[29]), "+f"(a[30]), "+f"(a[31])
#define ACC16_STR "{%0, %1, %2, %3, %4, %5, %6, %7, %8, %9, %10, %11, %12, %13, %14, %15}"
#define ACC32_STR                                                                                             \
    "{%0, %1, %2, %3, %4, %5, %6, %7, %8, %9, %10, %11, %12, %13, %14, %15, "                                 \
    "%16, %17, %18, %19, %20, %21, %22, %23, %24, %25, %26, %27, %28, %29, %30, %31}"

template <int BOFF>
__device__ __forceinline__ void wgmma_rs(float (&d)[32], uint32_t a0, uint32_t a1, uint32_t a2, uint32_t a3, uint32_t db_lo) {
    asm volatile("{\n.reg .b64 db;\n.reg .b32 lo;\n"
                 "add.u32 lo, %36, %37;\nmov.b64 db, {lo, 0x40000040};\n"
                 "wgmma.mma_async.sync.aligned.m64n64k16.f32.bf16.bf16 " ACC32_STR
                 ", {%32, %33, %34, %35}, db, 1, -1, 1, 0;\n}"
                 : ACC32(d) : "r"(a0), "r"(a1), "r"(a2), "r"(a3), "r"(db_lo), "n"(BOFF));
}
template <int ACCUM, int AOFF, int BOFF>
__device__ __forceinline__ void wgmma_ss(float (&d)[32], uint32_t da_lo, uint32_t db_lo) {
    asm volatile("{\n.reg .b64 da, db;\n.reg .b32 lo;\n"
                 "add.u32 lo, %32, %35;\nmov.b64 da, {lo, 0x40000040};\n"
                 "add.u32 lo, %33, %36;\nmov.b64 db, {lo, 0x40000040};\n"
                 "wgmma.mma_async.sync.aligned.m64n64k16.f32.bf16.bf16 " ACC32_STR
                 ", da, db, %34, 1, 1, 1, 0;\n}"
                 : ACC32(d) : "r"(da_lo), "r"(db_lo), "n"(ACCUM), "n"(AOFF), "n"(BOFF));
}
template <int ACCUM, int AOFF, int BOFF>
__device__ __forceinline__ void wgmma_ss32(float (&d)[16], uint32_t da_lo, uint32_t db_lo) {
    asm volatile("{\n.reg .b64 da, db;\n.reg .b32 lo;\n"
                 "add.u32 lo, %16, %19;\nmov.b64 da, {lo, 0x40000040};\n"
                 "add.u32 lo, %17, %20;\nmov.b64 db, {lo, 0x40000040};\n"
                 "wgmma.mma_async.sync.aligned.m64n32k16.f32.bf16.bf16 " ACC16_STR
                 ", da, db, %18, 1, 1, 1, 0;\n}"
                 : ACC16(d) : "r"(da_lo), "r"(db_lo), "n"(ACCUM), "n"(AOFF), "n"(BOFF));
}
__device__ __forceinline__ uint32_t desc_lo(uint32_t addr) { return ((addr & 0x3FFFFu) >> 4) | (1u << 16); }
__device__ __forceinline__ uint32_t pack_bf16(float lo, float hi) {
    uint32_t r;
    asm("cvt.rn.bf16x2.f32 %0, %1, %2;" : "=r"(r) : "f"(hi), "f"(lo));
    return r;
}
__device__ __forceinline__ uint32_t pack_neg(float lo, float hi) {
    const uint32_t v = pack_bf16(lo, hi) ^ 0x80008000u;
    return v == 0u ? 0x80008000u : v;
}
__device__ __forceinline__ float dup(float x, float one) {
    float r;
    asm volatile("mul.f32 %0, %1, %2;" : "=f"(r) : "f"(x), "f"(one));
    return r;
}
__device__ __forceinline__ void stsm_x4_t(uint32_t addr, uint32_t r0, uint32_t r1, uint32_t r2, uint32_t r3) {
    asm volatile("stmatrix.sync.aligned.m8n8.x4.trans.shared.b16 [%0], {%1, %2, %3, %4};"
                 ::"r"(addr), "r"(r0), "r"(r1), "r"(r2), "r"(r3) : "memory");
}

struct Ring {
    uint32_t so;
    uint32_t ph;
    __device__ __forceinline__ void advance() {
        so += 8;
        if (so == NSLOTS * 8) { so = 0; ph ^= 1; }
    }
    __device__ __forceinline__ uint32_t prev() const { return so == 0 ? (NSLOTS - 1) * 8 : so - 8; }
    __device__ __forceinline__ uint32_t back(uint32_t k) const { return so >= k * 8 ? so - k * 8 : so + (NSLOTS - k) * 8; }
};

struct Ctx {
    uint32_t sbase;
    uint32_t db0;
    uint32_t empty_tgt;
    bool     signal;
};

template <int KC, bool RS>
__device__ __forceinline__ void chunk(float (&acc)[32], const uint32_t (&W)[96], uint32_t da0, const Ctx& cx, Ring& rg, bool& ready) {
    if (!ready) mbar_wait(cx.sbase + OFF_FULL + rg.so, rg.ph);
    const uint32_t db = cx.db0 + rg.so * 64;
    const uint32_t prev = rg.prev();
    rg.advance();
    ready = ((EARLY >> KC) & 1) ? mbar_try(cx.sbase + OFF_FULL + rg.so, rg.ph) : false;
    wg_fence();
    if (RS) {
        wgmma_rs<0>(acc, W[KC * 16 + 0],  W[KC * 16 + 1],  W[KC * 16 + 2],  W[KC * 16 + 3],  db);
        wgmma_rs<2>(acc, W[KC * 16 + 4],  W[KC * 16 + 5],  W[KC * 16 + 6],  W[KC * 16 + 7],  db);
        wgmma_rs<4>(acc, W[KC * 16 + 8],  W[KC * 16 + 9],  W[KC * 16 + 10], W[KC * 16 + 11], db);
        wgmma_rs<6>(acc, W[KC * 16 + 12], W[KC * 16 + 13], W[KC * 16 + 14], W[KC * 16 + 15], db);
    } else {
        wgmma_ss<(KC > 0), (KC * 4 + 0) * 128, 0>(acc, da0, db);
        wgmma_ss<1,        (KC * 4 + 1) * 128, 2>(acc, da0, db);
        wgmma_ss<1,        (KC * 4 + 2) * 128, 4>(acc, da0, db);
        wgmma_ss<1,        (KC * 4 + 3) * 128, 6>(acc, da0, db);
    }
    wg_commit();
    if (KC > 0) {
        wg_wait<1>();
        if (cx.signal) mbar_arrive_cluster(cx.empty_tgt + prev);
    }
}

__device__ __forceinline__ void chunk_q5(float (&acc)[32], int wg, const Ctx& cx, Ring& rg, bool& ready) {
    Ring r = rg;
    const uint32_t db = cx.db0 + r.so * 64;
    uint32_t da = 0;
    bool ok = ((EARLY >> 4) & 1) ? ready : mbar_try(cx.sbase + OFF_FULL + r.so, r.ph);
#pragma unroll
    for (int g = 0; g < 3; g++) {
        r.advance();
        ok = mbar_try(cx.sbase + OFF_FULL + r.so, r.ph) && ok;
        if (g == wg) da = cx.db0 + r.so * 64;
    }
    if (!ok) {
        Ring t = rg;
#pragma unroll 1
        for (int g = 0; g < 4; g++) {
            mbar_wait(cx.sbase + OFF_FULL + t.so, t.ph);
            t.advance();
        }
    }
    r.advance();
    ready = ((EARLY >> 5) & 1) ? mbar_try(cx.sbase + OFF_FULL + r.so, r.ph) : false;
    wg_fence();
    wgmma_ss<1, 0 * 128, 0>(acc, da, db);
    wgmma_ss<1, 1 * 128, 2>(acc, da, db);
    wgmma_ss<1, 2 * 128, 4>(acc, da, db);
    wgmma_ss<1, 3 * 128, 6>(acc, da, db);
    wg_commit();
    wg_wait<1>();
    if (cx.signal) mbar_arrive_cluster(cx.empty_tgt + rg.prev());
    rg = r;
}
__device__ __forceinline__ void finish_q(const Ctx& cx, const Ring& rg) {
    wg_wait<0>();
    if (cx.signal) {
        mbar_arrive_cluster(cx.empty_tgt + rg.back(4));
        mbar_arrive_cluster(cx.empty_tgt + rg.back(3));
        mbar_arrive_cluster(cx.empty_tgt + rg.back(2));
        mbar_arrive_cluster(cx.empty_tgt + rg.back(1));
    }
}

__global__ void __cluster_dims__(2, 1, 1) __launch_bounds__(NTHREADS, 1)
fpn_kernel(Scratch* scr, const __nv_bfloat16* __restrict__ wo_ptr,
           const __nv_bfloat16* __restrict__ c_ptr, const __nv_bfloat16* __restrict__ p_ptr, const int maxfine, const float one,
           const __grid_constant__ CUtensorMap tm_w64, const __grid_constant__ CUtensorMap tm_wl3,
           const __grid_constant__ CUtensorMap tm_p8, const __grid_constant__ CUtensorMap tm_c,
           const __grid_constant__ CUtensorMap tm_p, const __grid_constant__ CUtensorMap tm_out)
{
    extern __shared__ __align__(1024) uint8_t smem[];
    const uint32_t sbase = smem_u32(smem);
    const int tid   = threadIdx.x;
    const int warp  = __shfl_sync(0xffffffffu, tid >> 5, 0);
    const int lane  = tid & 31;
    const int rank  = blockIdx.x & 1;
    const int pair  = blockIdx.x >> 1;
    const int npair = gridDim.x >> 1;

    const int nfine = maxfine - ((maxfine - 1) * npair + pair >= NSEG);
    auto seg_row = [](int g) { const int y = g / 12; return y * (2 * HW) + (g - y * 12) * 32; };

    if (tid == 480) {
        prefetch_tmap(&tm_w64); prefetch_tmap(&tm_wl3); prefetch_tmap(&tm_p8);
        prefetch_tmap(&tm_c); prefetch_tmap(&tm_p); prefetch_tmap(&tm_out);
    }
    auto first_loads = [&]() {
        const int g0 = pair % 3;
#pragma unroll 1
        for (int s = 0; s < 3; s++) {
            const uint32_t bar = sbase + OFF_FULL + s * 8;
            const uint32_t dst = sbase + OFF_WOUT + g0 * WOUT_SLICE + s * 16384;
            mbar_expect_tx(bar, pair < NJOBS ? 3 * SLOT_BYTES : 2 * SLOT_BYTES);
            tma_load_2d(dst, &tm_w64, rank * 192 + g0 * 64, s * 128, bar);
            if (pair < NJOBS) tma_load_3d(sbase + OFF_RING + s * SLOT_BYTES, &tm_wl3, 0, (pair / 3) * 32, 2 * s, bar);
            tma_load_2d(s < 2 ? dst + 8192 : sbase + OFF_STAGE + g0 * 8192, &tm_w64, rank * 192 + g0 * 64, s * 128 + 64, bar);
        }
    };
    if (tid == 384) {
        for (int s = 0; s < 3; s++) mbar_init(sbase + OFF_FULL + s * 8, 1);
        asm volatile("fence.mbarrier_init.release.cluster;" ::: "memory");
        asm volatile("fence.proxy.async.shared::cta;" ::: "memory");
        if (FIRST_EARLY) { TSTAMP(3, 5); first_loads(); }
    }
    if (warp == 13) {
        if (lane == 0) {
            for (int s = 0; s < NSLOTS; s++) {
                if (s >= 3) mbar_init(sbase + OFF_FULL + s * 8, 1);
                mbar_init(sbase + OFF_EMPTY + s * 8, 6);
            }
            for (int g = 0; g < 3; g++) mbar_init(sbase + OFF_WBAR + g * 8, 1);
            mbar_init(sbase + OFF_JB2, 1);
            asm volatile("st.volatile.shared.u32 [%0], %1;" ::"r"(sbase + OFF_PACE), "r"(6) : "memory");
            asm volatile("fence.mbarrier_init.release.cluster;" ::: "memory");
            asm volatile("fence.proxy.async.shared::cta;" ::: "memory");
        }
        __syncwarp();
        asm volatile("bar.arrive 5, 448;" ::: "memory");
        if (lane == 0) TSTAMP(3, 4);
    }
    __syncwarp();
    asm volatile("barrier.cluster.arrive.relaxed.aligned;" ::: "memory");
    if (warp >= 12) {
        asm volatile("setmaxnreg.dec.sync.aligned.u32 32;");
        if (PEARLY && tid == 416) {
            if (PEARLY > 1) __nanosleep(PEARLY);
#pragma unroll 1
            for (int kc = 0; kc < 6; kc++) {
                const uint32_t bar = sbase + OFF_FULL + (3 + kc) * 8;
                mbar_expect_tx(bar, 3 * SLOT_BYTES);
                tma_load_5d(sbase + OFF_RING + (3 + kc) * SLOT_BYTES, &tm_p8, kc * 64, pair * 2, 0, bar);
            }
        }
        if (warp == 12) {
            if (!FIRST_EARLY && lane == 0) { TSTAMP(3, 5); first_loads(); }
            __syncwarp();
            asm volatile("bar.sync 5, 448;" ::: "memory");
        }
        if (tid == 384) {
            const int g1 = (pair + 1) % 3, g2 = (pair + 2) % 3;
            if (HOLD) __nanosleep(HOLD);
            TSTAMP(3, 6);
#pragma unroll 1
            for (int kc = 0; kc < 6; kc++) {
                const uint32_t bar = sbase + OFF_FULL + (3 + kc) * 8;
                if (!PEARLY) {
                    mbar_expect_tx(bar, 3 * SLOT_BYTES);
                    tma_load_5d(sbase + OFF_RING + (3 + kc) * SLOT_BYTES, &tm_p8, kc * 64, pair * 2, 0, bar);
                }
                tma_load_2d(kc < 5 ? sbase + OFF_WOUT + g1 * WOUT_SLICE + kc * 8192 : sbase + OFF_STAGE + g1 * 8192,
                            &tm_w64, rank * 192 + g1 * 64, kc * 64, bar);
                tma_load_2d(kc < 5 ? sbase + OFF_WOUT + g2 * WOUT_SLICE + kc * 8192 : sbase + OFF_STAGE + g2 * 8192,
                            &tm_w64, rank * 192 + g2 * 64, kc * 64, bar);
            }
        }
        if (tid == 384) TSTAMP(3, 1);
        __syncwarp();
        asm volatile("barrier.cluster.wait.aligned;" ::: "memory");
        if (warp == 12) {
            if (lane == 0) {
                TSTAMP(3, 2);
                const uint32_t dst0 = sbase + OFF_RING + rank * 4096;
                uint32_t so = 9 * 8, ph = 1, step = 6;
                LSTAMP(0, 0);
                auto acquire = [&](uint32_t& bar, uint32_t& dst) {
                    bar = sbase + OFF_FULL + so;
                    dst = dst0 + so * (SLOT_BYTES / 8);
                    mbar_wait_bounded(sbase + OFF_EMPTY + so, ph);
                    mbar_expect_tx(bar, SLOT_BYTES);
                };
                auto advance = [&]() {
                    so += 8;
                    if (so == NSLOTS * 8) { so = 0; ph ^= 1; }
                    step++;
                    asm volatile("st.volatile.shared.u32 [%0], %1;" ::"r"(sbase + OFF_PACE), "r"(step) : "memory");
                };
                unsigned mytiles = 0, seen = 0;
                const unsigned maxtiles = maxfine + (maxfine - 1) / 4;
                auto govern = [&]() {
                    if (rank == 0) {
                        unsigned spins = 0;
                        while (mytiles >= GOV_START && (int)(mytiles * npair - seen) > GOV_SLACK && ++spins < 100000u)
                            asm volatile("ld.relaxed.gpu.global.u32 %0, [%1];" : "=r"(seen) : "l"(&scr->prog) : "memory");
                        mytiles++;
                        if (GOV_INC < 0) asm volatile("red.relaxed.gpu.global.add.u32 [%0], 1;" ::"l"(&scr->prog) : "memory");
                        if (GOV_POS < 0)
                        asm volatile("ld.relaxed.gpu.global.u32 %0, [%1];" : "=r"(seen) : "l"(&scr->prog) : "memory");
                    }
                };
#pragma unroll 1
                for (int j = 0; j < nfine; j++) {
                    const uint64_t pol = ((j >= EF_FROM && j < EF_TO) || j >= EF_TAIL) ? POLICY_EVICT_FIRST : POLICY_EVICT_NORMAL;
                    if ((j & 3) == 0 && j > 0) {
                        const int jc = X_SAME ? 2 * rank : (j + 2 * rank < nfine) ? j + 2 * rank : maxfine;
                        govern();
#pragma unroll
                        for (int kc = 0; kc < 6; kc++) {
                            uint32_t bar, dst;
                            acquire(bar, dst);
                            tma_load_5d_mc(dst, &tm_p, kc * 64, pair * 2, jc, bar, pol);
                            advance();
                            if (GOV_INC >= 0 && kc == GOV_INC + GOV_QOFF && rank == 0) asm volatile("red.relaxed.gpu.global.add.u32 [%0], 1;" ::"l"(&scr->prog) : "memory");
                            if (GOV_POS >= 0 && kc == GOV_POS + 3 && rank == 0)
                                asm volatile("ld.relaxed.gpu.global.u32 %0, [%1];" : "=r"(seen) : "l"(&scr->prog) : "memory");
                        }
#pragma unroll
                        for (int g = 0; g < 3; g++) {
                            uint32_t bar, dst;
                            acquire(bar, dst);
                            tma_load_2d(dst - rank * 4096, &tm_w64, rank * 192 + g * 64, 320, bar);
                            so += 8;
                            if (so == NSLOTS * 8) { so = 0; ph ^= 1; }
                            if (GOV_POS >= 0 && g == GOV_POS - 3 && rank == 0)
                                asm volatile("ld.relaxed.gpu.global.u32 %0, [%1];" : "=r"(seen) : "l"(&scr->prog) : "memory");
                        }
                    }
                    const int row = seg_row((X_SAME ? 0 : j) * npair + pair) + rank * HW;
                    govern();
#pragma unroll
                    for (int kc = 0; kc < 6; kc++) {
                        uint32_t bar, dst;
                        acquire(bar, dst);
                        tma_load_2d_mc(dst, &tm_c, kc * 64, row, bar, pol);
                        advance();
                        if (kc == GOV_INC && rank == 0 && j + 1 < maxfine) asm volatile("red.relaxed.gpu.global.add.u32 [%0], 1;" ::"l"(&scr->prog) : "memory");
                        if (kc == GOV_POS && rank == 0)
                            asm volatile("ld.relaxed.gpu.global.u32 %0, [%1];" : "=r"(seen) : "l"(&scr->prog) : "memory");
                    }
                }
                if (rank == 0) {
                    const unsigned rest = maxtiles - mytiles + (nfine == maxfine);
                    if (atomicAdd(&scr->prog, rest) + rest == maxtiles * npair) {
                        asm volatile("st.relaxed.gpu.global.u32 [%0], 0;" ::"l"(&scr->prog) : "memory");
                        asm volatile("red.relaxed.gpu.global.add.u32 [%0], 1;" ::"l"(&scr->epoch) : "memory");
                    }
                }
                for (int s = 0; s < NSLOTS; s++) {
                    mbar_wait_bounded(sbase + OFF_EMPTY + so, ph);
                    so += 8;
                    if (so == NSLOTS * 8) { so = 0; ph ^= 1; }
                }
                TSTAMP(3, 3); TDUMP(3);
            }
        } else if (warp == 13) {
            const int ntiles = nfine + (nfine + 3) / 4;
            uint32_t sink = 0, pv = 0;
#pragma unroll 1
            for (int i = PF_SKIP1; i < (X_SAME ? 0 : ntiles); i++) {
                const int k5 = i / 5, t = i - k5 * 5;
                const char *b0, *b1;
                if (t == 0) {
                    const int g = min((4 * k5 + 2 * rank) * npair + pair, NSEG - 1);
                    b0 = (const char*)p_ptr + (size_t)g * (16 * C * 2);
                    b1 = (const char*)p_ptr + (size_t)min(g + npair, NSEG - 1) * (16 * C * 2);
                } else {
                    b0 = (const char*)c_ptr + (size_t)(seg_row((4 * k5 + t - 1) * npair + pair) + rank * HW) * (C * 2);
                    b1 = b0 + 16 * C * 2;
                }
                const int extra = PF_LEAD0 - PF_LEAD - (i > PF_DECAY ? (i - PF_DECAY) * PF_RATE / 2 : 0);
                int need = 6 * i - PF_LEAD - (extra > 0 ? extra : 0);
                if (need < PF_FIRST) need = PF_FIRST;
                unsigned spins = 0;
                while (true) {
                    uint32_t v;
                    asm volatile("ld.volatile.shared.u32 %0, [%1];" : "=r"(v) : "r"(sbase + OFF_PACE) : "memory");
                    if ((int)v >= need || ++spins > 4000000u) break;
                    __nanosleep(20);
                }
                if (lane == 0) LSTAMP(2, i);
#pragma unroll
                for (int k = 0; k < 6; k++) {
                    if (i <= PF_IB) {
                        if (lane == 0) asm volatile("cp.async.bulk.prefetch.L2.global [%0], 4096;" ::"l"((k < 3 ? b0 : b1) + (k % 3) * 4096) : "memory");
                    } else
                    asm volatile("prefetch.global.L2 [%0];" ::"l"((k < 3 ? b0 : b1) + lane * 128 + (k % 3) * 4096) : "memory");
                    __nanosleep(i <= PF_I0 ? PF_GAP0 : i <= PF_I1 ? PF_GAP1 : PF_GAP);
                }
                if (W5MODE == 0) {
                if (t == 0) {
#pragma unroll
                    for (int k = 0; k < 6; k++) {
                        const int idx = k * 32 + lane;
                        asm volatile("prefetch.global.L2 [%0];" ::"l"((const char*)wo_ptr + (320 + idx / 3) * (C * 2) + rank * 384 + (idx % 3) * 128) : "memory");
                    }
                }
                } else if (W5MODE == 2 || W5MODE == 3) {
                    const int idx = ((pair + i * 5) % (192 / W5N)) * W5N + lane;
                    if (lane < W5N && ((W5MASK >> t) & 1) && i >= W5FROM) {
                        sink ^= pv;
                        asm volatile("ld.global.cg.u32 %0, [%1];" : "=r"(pv) : "l"((const char*)wo_ptr + (320 + idx / 3) * (C * 2) + rank * 384 + (idx % 3) * 128) : "memory");
                    }
                } else if (W5MODE == 4) {
                    const int idx = (pair % 6) * 32 + lane;
                    if (t == W5T)
                        asm volatile("prefetch.global.L2 [%0];" ::"l"((const char*)wo_ptr + (320 + idx / 3) * (C * 2) + rank * 384 + (idx % 3) * 128) : "memory");
                }
            }
            asm volatile("st.volatile.shared.u32 [%0], %1;" ::"r"(sbase + OFF_PACE + 4), "r"(sink ^ pv) : "memory");
        }
        else if (warp == 15) {
            uint32_t par, v;
            asm volatile("ld.relaxed.gpu.global.u32 %0, [%1];" : "=r"(par) : "l"(&scr->epoch) : "memory");
            uint4* clr = scr->wfrag + (~par & 1) * (6 * 24 * 128);
            unsigned spins = 0;
            do {
                __nanosleep(500);
                asm volatile("ld.volatile.shared.u32 %0, [%1];" : "=r"(v) : "r"(sbase + OFF_PACE) : "memory");
            } while (v < CLR_AT && ++spins < 100000u);
            for (int i = blockIdx.x * 32 + lane; i < 6 * 24 * 128; i += gridDim.x * 32) clr[i] = make_uint4(0u, 0u, 0u, 0u);
        }
    } else {
        uint32_t par;
        asm volatile("ld.relaxed.gpu.global.u32 %0, [%1];" : "=r"(par) : "l"(&scr->epoch) : "memory");
        asm volatile("setmaxnreg.inc.sync.aligned.u32 160;");
        asm volatile("bar.sync 5, 448;" ::: "memory");
        const int wg   = warp >> 2;
        const int wtid = tid & 127;
        Ctx cx;
        cx.sbase     = sbase;
        cx.db0       = desc_lo(sbase + OFF_RING);
        cx.empty_tgt = mapa(sbase + OFF_EMPTY, warp & 1);
        cx.signal    = (lane == 0) && ((warp & 3) < 2);
        const uint32_t da0 = desc_lo(sbase + OFF_WOUT + wg * WOUT_SLICE);
        const int cb = rank * 3 + wg;

        float    acc[32];
        uint32_t qp[16];
        uint32_t W[96];
        Ring rg{0u, 0u};

        const uint32_t da5 = desc_lo(sbase + OFF_STAGE + wg * 8192) - 20 * 128;

        if (wtid == 0) TSTAMP(wg, 0);
        {
            uint32_t jph = 0;
            for (int job = pair; job < NJOBS; job += npair) {
                if (job % 3 == wg) {
                    if (job != pair) {
                        named_bar(wg);
                        if (wtid == 0) {
                            mbar_expect_tx(sbase + OFF_JB2, 6 * 4096);
                            for (int s = 0; s < 3; s++)
                                tma_load_3d(sbase + OFF_RING + s * SLOT_BYTES, &tm_wl3, 0, (job / 3) * 32, 2 * s, sbase + OFF_JB2);
                        }
                        for (int kc = 0; kc < 6; kc++) mbar_wait(sbase + OFF_FULL + (3 + kc) * 8, 0);
                        mbar_wait(sbase + OFF_JB2, jph);
                    }
                    float ja[16];
#define JOBK(k) wgmma_ss32<((k) > 0), (k) * 128, ((k) >> 2) * 256 + ((k) & 3) * 2>(ja, (k) < 20 ? da0 : da5, cx.db0);
                    mbar_wait(sbase + OFF_FULL, 0);
                    if (wtid == 0) TSTAMP(wg, 46);
                    wg_fence();
                    JOBK(0)  JOBK(1)  JOBK(2)  JOBK(3)  JOBK(4)  JOBK(5)  JOBK(6)  JOBK(7)
                    wg_commit();
                    mbar_wait(sbase + OFF_FULL + 8, 0);
                    wg_fence();
                    JOBK(8)  JOBK(9)  JOBK(10) JOBK(11) JOBK(12) JOBK(13) JOBK(14) JOBK(15)
                    wg_commit();
                    mbar_wait(sbase + OFF_FULL + 16, 0);
                    if (wtid == 0) TSTAMP(wg, 47);
                    wg_fence();
                    JOBK(16) JOBK(17) JOBK(18) JOBK(19) JOBK(20) JOBK(21) JOBK(22) JOBK(23)
#undef JOBK
                    wg_commit();
                    wg_wait<0>();
                    if (wtid == 0) TSTAMP(wg, 48);
                    const int fidx = (cb * 24 + (job / 3) * 2) * 128 + wtid;
                    uint4* dst = scr->wfrag + (par & 1) * (6 * 24 * 128) + fidx;
#pragma unroll
                    for (int i = 0; i < 2; i++) {
                        asm volatile("st.relaxed.gpu.global.v4.u32 [%0], {%1, %2, %3, %4};" ::"l"(dst + i * 128),
                                     "r"(pack_neg(ja[8 * i + 0], ja[8 * i + 1])), "r"(pack_neg(ja[8 * i + 2], ja[8 * i + 3])),
                                     "r"(pack_neg(ja[8 * i + 4], ja[8 * i + 5])), "r"(pack_neg(ja[8 * i + 6], ja[8 * i + 7])) : "memory");
                    }
                }
                if (job % 3 == wg && wtid == 0) TSTAMP(wg, 49);
                if (job + npair < NJOBS) asm volatile("bar.sync 4, 384;" ::: "memory");
                if (job != pair) jph ^= 1;
            }
        }

        par &= 1;
        if (JOBPRIO && pair < NJOBS) asm volatile("bar.sync 6, 384;" ::: "memory");
        if (wtid == 0) TSTAMP(wg, 1);
        asm volatile("barrier.cluster.wait.aligned;" ::: "memory");

        mbar_wait(sbase + OFF_FULL, 0);
        mbar_wait(sbase + OFF_FULL + 8, 0);
        mbar_wait(sbase + OFF_FULL + 16, 0);
        if (cx.signal) {
            mbar_arrive_cluster(cx.empty_tgt);
            mbar_arrive_cluster(cx.empty_tgt + 8);
            mbar_arrive_cluster(cx.empty_tgt + 16);
        }
        rg.so = 3 * 8;
        bool ready = false;

        const uint4* wsrc = scr->wfrag + (par * 6 + cb) * (24 * 128) + wtid;
        auto load_w = [&](int kc) {
#pragma unroll
            for (int s = 4 * kc; s < 4 * kc + 4; s++) {
                asm volatile("ld.relaxed.gpu.global.v4.u32 {%0, %1, %2, %3}, [%4];"
                             : "=r"(W[4 * s]), "=r"(W[4 * s + 1]), "=r"(W[4 * s + 2]), "=r"(W[4 * s + 3])
                             : "l"(wsrc + s * 128) : "memory");
            }
        };
        auto load_at = [&](int pos) {
            if (WL0 == pos) load_w(0);
            if (WL1 == pos) load_w(1);
            if (WL2 == pos) load_w(2);
            if (WL3 == pos) load_w(3);
            if (WL4 == pos) load_w(4);
            if (WL5 == pos) {
                if (!W5TMA) load_w(5);
                else {
                    mbar_wait(sbase + OFF_WBAR + wg * 8, 0);
#pragma unroll
                    for (int s = 0; s < 4; s++) {
                        uint32_t* w = W + 80 + 4 * s;
                        asm volatile("ld.shared.v4.u32 {%0, %1, %2, %3}, [%4];" : "=r"(w[0]), "=r"(w[1]), "=r"(w[2]), "=r"(w[3])
                                     : "r"(sbase + OFF_STAGE + wg * 8192 + wtid * 16 + s * 2048) : "memory");
                    }
                }
            }
        };
        auto check_w = [&](int kc) {
            uint32_t* w = W + 16 * kc;
            asm volatile(
                "{\n.reg .pred p;\n.reg .u32 m, n;\n"
                "mov.u32 n, 0;\n"
                "CHK_%=:\n"
                "min.u32 m, %0, %1;\n min.u32 m, m, %2;\n min.u32 m, m, %3;\n min.u32 m, m, %4;\n min.u32 m, m, %5;\n"
                "min.u32 m, m, %6;\n min.u32 m, m, %7;\n min.u32 m, m, %8;\n min.u32 m, m, %9;\n min.u32 m, m, %10;\n"
                "min.u32 m, m, %11;\n min.u32 m, m, %12;\n min.u32 m, m, %13;\n min.u32 m, m, %14;\n min.u32 m, m, %15;\n"
                "setp.ne.u32 p, m, 0;\n"
                "vote.sync.all.pred p, p, 0xffffffff;\n"
                "@p bra.uni OK_%=;\n"
                "add.u32 n, n, 1;\n"
                "setp.gt.u32 p, n, 5000000;\n"
                "@p bra.uni OK_%=;\n"
                "ld.relaxed.gpu.global.v4.u32 {%0, %1, %2, %3}, [%16];\n"
                "ld.relaxed.gpu.global.v4.u32 {%4, %5, %6, %7}, [%16 + 2048];\n"
                "ld.relaxed.gpu.global.v4.u32 {%8, %9, %10, %11}, [%16 + 4096];\n"
                "ld.relaxed.gpu.global.v4.u32 {%12, %13, %14, %15}, [%16 + 6144];\n"
                "bra.uni CHK_%=;\n"
                "OK_%=:\n}"
                : "+r"(w[0]), "+r"(w[1]), "+r"(w[2]), "+r"(w[3]), "+r"(w[4]), "+r"(w[5]), "+r"(w[6]), "+r"(w[7]),
                  "+r"(w[8]), "+r"(w[9]), "+r"(w[10]), "+r"(w[11]), "+r"(w[12]), "+r"(w[13]), "+r"(w[14]), "+r"(w[15])
                : "l"(wsrc + kc * 512) : "memory");
        };
        {
            chunk<0, false>(acc, W, da0, cx, rg, ready);
            if (wtid == 0) TSTAMP(wg, 50);
            load_at(0);
            chunk<1, false>(acc, W, da0, cx, rg, ready);
            load_at(1);
            chunk<2, false>(acc, W, da0, cx, rg, ready);
            if (wtid == 0) TSTAMP(wg, 51);
            load_at(2);
            chunk<3, false>(acc, W, da0, cx, rg, ready);
            load_at(3);
            chunk<4, false>(acc, W, da0, cx, rg, ready);
            if (wtid == 0) TSTAMP(wg, 52);
            load_at(4);
            chunk<5, false>(acc, W, da5, cx, rg, ready);
            load_at(5);
            wg_wait<0>();
            if (cx.signal) mbar_arrive_cluster(cx.empty_tgt + rg.prev());
            if (W5TMA && wtid == 64) {
                mbar_expect_tx(sbase + OFF_WBAR + wg * 8, 8192);
                asm volatile("cp.async.bulk.shared::cluster.global.mbarrier::complete_tx::bytes [%0], [%1], 8192, [%2];"
                             ::"r"(sbase + OFF_STAGE + wg * 8192), "l"(wsrc - 64 + 20 * 128), "r"(sbase + OFF_WBAR + wg * 8) : "memory");
            }
#pragma unroll
            for (int j = 0; j < 16; j++) qp[j] = pack_bf16(acc[2 * j], acc[2 * j + 1]);
            if (wtid == 0) TSTAMP(wg, 2);
        }

        const uint32_t stage = sbase + OFF_STAGE + wg * 8192;
        const uint32_t st_addr = stage + (((lane >> 4) * 8 + (lane & 7)) << 7)
                               + (((((warp & 3) << 1) | ((lane >> 3) & 1)) ^ (lane & 7)) << 4);
        auto flush_part = [&](int row, int part) {
            if (part == 0) {
                asm volatile("fence.proxy.async.shared::cta;" ::: "memory");
                named_bar(wg);
            }
            if (wtid == 0) {
                tma_store_2d(&tm_out, cb * 64, row + (part >> 1) * HW + (part & 1) * 16, stage + part * 2048, (ST_NFROM < 99 && row >= ST_NFROM * 4224) ? POLICY_EVICT_NORMAL : POLICY_EVICT_FIRST);
                if (COMMIT1 == 0 || (COMMIT1 == 1 && part == 3)) asm volatile("cp.async.bulk.commit_group;" ::: "memory");
            }
        };

        auto init_acc = [&]() {
#pragma unroll
            for (int b = 0; b < 2; b++) {
#pragma unroll
                for (int h = 0; h < 2; h++) {
                    const uint32_t q = qp[b * 2 + h];
                    const float lo = __uint_as_float(q << 16), hi = __uint_as_float(q & 0xffff0000u);
#pragma unroll
                    for (int dy = 0; dy < 2; dy++) {
                        acc[16 * dy + 8 * b + 2 * h]         = (FMULI && dy) ? dup(lo, one) : lo;
                        acc[16 * dy + 8 * b + 2 * h + 1]     = FMULI ? dup(lo, one) : lo;
                        acc[16 * dy + 8 * b + 4 + 2 * h]     = (FMULI && dy) ? dup(hi, one) : hi;
                        acc[16 * dy + 8 * b + 4 + 2 * h + 1] = FMULI ? dup(hi, one) : hi;
                    }
                }
            }
#pragma unroll
            for (int i = 0; i < 12; i++) qp[i] = qp[i + 4];
        };
        auto stage_tile = [&]() {
            wg_wait<0>();
            if (cx.signal) mbar_arrive_cluster(cx.empty_tgt + rg.prev());
#pragma unroll
            for (int i = 0; i < 8; i += 2) {
                stsm_x4_t(st_addr + i * 1024,
                          pack_bf16(acc[4 * i + 0], acc[4 * i + 1]), pack_bf16(acc[4 * i + 2], acc[4 * i + 3]),
                          pack_bf16(acc[4 * i + 4], acc[4 * i + 5]), pack_bf16(acc[4 * i + 6], acc[4 * i + 7]));
            }
        };

        init_acc();
        check_w(0);
        if (wtid == 0) TSTAMP(wg, 3);
        chunk<0, true>(acc, W, da0, cx, rg, ready);
        load_at(6);
        check_w(1);
        chunk<1, true>(acc, W, da0, cx, rg, ready);
        load_at(7);
        check_w(2);
        chunk<2, true>(acc, W, da0, cx, rg, ready);
        load_at(8);
        check_w(3);
        chunk<3, true>(acc, W, da0, cx, rg, ready);
        load_at(9);
        check_w(4);
        chunk<4, true>(acc, W, da0, cx, rg, ready);
        check_w(5);
        if (wtid == 0) TSTAMP(wg, 4);
        chunk<5, true>(acc, W, da0, cx, rg, ready);
        int prow = seg_row(pair);
        int j = 1;
        while (true) {
            if (wtid == 0) {
                if (COMMIT1 == 2) asm volatile("cp.async.bulk.commit_group;" ::: "memory");
                asm volatile("cp.async.bulk.wait_group.read 0;" ::: "memory");
            }
            named_bar(wg);
            if (j >= nfine) break;
            const bool pend = (j & 3) != 0;
            if (!((EARLY >> 5) & 1)) ready = mbar_try(sbase + OFF_FULL + rg.so, rg.ph);
            auto flush_at = [&](int pos, bool q) {
                if ((q ? SQ0 : SP0) == pos) flush_part(prow, 0);
                if ((q ? SQ1 : SP1) == pos) flush_part(prow, 1);
                if ((q ? SQ2 : SP2) == pos) flush_part(prow, 2);
                if ((q ? SQ3 : SP3) == pos) flush_part(prow, 3);
            };
            if (pend) {
                stage_tile();
                init_acc();
                chunk<0, true>(acc, W, da0, cx, rg, ready);
                flush_at(0, false);
            } else {
                stage_tile();
                chunk<0, false>(acc, W, da0, cx, rg, ready);
                flush_at(0, true);
                chunk<1, false>(acc, W, da0, cx, rg, ready);
                flush_at(1, true);
                chunk<2, false>(acc, W, da0, cx, rg, ready);
                flush_at(2, true);
                chunk<3, false>(acc, W, da0, cx, rg, ready);
                flush_at(3, true);
                chunk<4, false>(acc, W, da0, cx, rg, ready);
                flush_at(4, true);
                chunk_q5(acc, wg, cx, rg, ready);
                flush_at(5, true);
                finish_q(cx, rg);
#pragma unroll
                for (int i = 0; i < 16; i++) qp[i] = pack_bf16(acc[2 * i], acc[2 * i + 1]);
                init_acc();
                chunk<0, true>(acc, W, da0, cx, rg, ready);
                flush_at(6, true);
            }
            chunk<1, true>(acc, W, da0, cx, rg, ready);
            if (pend) flush_at(1, false); else flush_at(7, true);
            chunk<2, true>(acc, W, da0, cx, rg, ready);
            if (pend) flush_at(2, false); else flush_at(8, true);
            chunk<3, true>(acc, W, da0, cx, rg, ready);
            if (pend) flush_at(3, false); else flush_at(9, true);
            chunk<4, true>(acc, W, da0, cx, rg, ready);
            if (pend) flush_at(4, false); else flush_at(10, true);
            chunk<5, true>(acc, W, da0, cx, rg, ready);
            prow = seg_row((X_SAME ? 0 : j) * npair + pair);
            j++;
        }
        stage_tile();
#pragma unroll
        for (int part = 0; part < 4; part++) flush_part(prow, part);
        if (wtid == 0) {
            if (COMMIT1 == 2) asm volatile("cp.async.bulk.commit_group;" ::: "memory");
            asm volatile("cp.async.bulk.wait_group.read 0;" ::: "memory");
        }
        if (wtid == 0) { TSTAMP(wg, 45); TDUMP(wg); }
    }
}

typedef CUresult (*EncodeFn)(CUtensorMap*, CUtensorMapDataType, cuuint32_t, void*, const cuuint64_t*, const cuuint64_t*,
                             const cuuint32_t*, const cuuint32_t*, CUtensorMapInterleave, CUtensorMapSwizzle,
                             CUtensorMapL2promotion, CUtensorMapFloatOOBfill);

void encode(EncodeFn fn, CUtensorMap* tm, const void* ptr, int rank, const cuuint64_t* dims, const cuuint64_t* strides,
            const cuuint32_t* box) {
    const cuuint32_t es[5] = {1, 1, 1, 1, 1};
    fn(tm, CU_TENSOR_MAP_DATA_TYPE_BFLOAT16, (cuuint32_t)rank, const_cast<void*>(ptr), dims, strides, box, es,
       CU_TENSOR_MAP_INTERLEAVE_NONE, CU_TENSOR_MAP_SWIZZLE_128B, CU_TENSOR_MAP_L2_PROMOTION_NONE,
       CU_TENSOR_MAP_FLOAT_OOB_FILL_NONE);
}

}

extern "C" void kernel_launch(void* const* d_in, const int* in_sizes, int n_in, void* d_out, int out_size) {
    (void)in_sizes; (void)n_in; (void)out_size;
    const __nv_bfloat16* c_fine   = (const __nv_bfloat16*)d_in[0];
    const __nv_bfloat16* p_coarse = (const __nv_bfloat16*)d_in[1];
    const __nv_bfloat16* w_lat    = (const __nv_bfloat16*)d_in[2];
    const __nv_bfloat16* w_out    = (const __nv_bfloat16*)d_in[3];

    static EncodeFn fn = nullptr;
    static int grid = 0;
    static Scratch* scr = nullptr;
    if (!fn) {
        void* p = nullptr;
        cudaDriverEntryPointQueryResult qr;
        cudaGetDriverEntryPoint("cuTensorMapEncodeTiled", &p, cudaEnableDefault, &qr);
        fn = (EncodeFn)p;
        cudaGetSymbolAddress((void**)&scr, g_scratch);
        cudaFuncSetAttribute(fpn_kernel, cudaFuncAttributeMaxDynamicSharedMemorySize, SMEM_BYTES);
        cudaLaunchConfig_t cfg = {};
        cfg.gridDim = dim3(2); cfg.blockDim = dim3(NTHREADS); cfg.dynamicSmemBytes = SMEM_BYTES;
        cudaLaunchAttribute at[1];
        at[0].id = cudaLaunchAttributeClusterDimension;
        at[0].val.clusterDim.x = 2; at[0].val.clusterDim.y = 1; at[0].val.clusterDim.z = 1;
        cfg.attrs = at; cfg.numAttrs = 1;
        int ncl = 0;
        if (cudaOccupancyMaxActiveClusters(&ncl, fpn_kernel, &cfg) != cudaSuccess || ncl < 1) ncl = 1;
        if (ncl >= MAXPAIRS) ncl = MAXPAIRS;
        else while ((NSEG / 4) % ncl) ncl--;
        grid = 2 * ncl;
    }

    CUtensorMap tm_c, tm_p, tm_wl3, tm_out, tm_p8, tm_w64;
    {
        const cuuint64_t dims[2] = {(cuuint64_t)C, (cuuint64_t)NPIX};
        const cuuint64_t str[1]  = {(cuuint64_t)C * 2};
        const cuuint32_t box_in[2]  = {64, 32};
        const cuuint32_t box_out[2] = {64, 16};
        encode(fn, &tm_c, c_fine, 2, dims, str, box_in);
        encode(fn, &tm_out, d_out, 2, dims, str, box_out);
    }
    {
        const int np = grid / 2;
        const cuuint64_t dims[5] = {(cuuint64_t)C, 2, 4, (cuuint64_t)(2 * np), (cuuint64_t)((NSEG + np - 1) / np)};
        const cuuint64_t str[4]  = {(cuuint64_t)4 * C * 2, (cuuint64_t)C * 2, (cuuint64_t)8 * C * 2, (cuuint64_t)np * 16 * C * 2};
        const cuuint32_t box[5]  = {64, 2, 4, 2, 2};
        encode(fn, &tm_p, p_coarse, 5, dims, str, box);
        const cuuint32_t box8[5] = {64, 2, 4, 2, 4};
        encode(fn, &tm_p8, p_coarse, 5, dims, str, box8);
    }
    {
        const cuuint64_t dims[2] = {(cuuint64_t)C, (cuuint64_t)C};
        const cuuint64_t str[1]  = {(cuuint64_t)C * 2};
        const cuuint32_t box_k[2] = {64, 64};
        encode(fn, &tm_w64, w_out, 2, dims, str, box_k);
    }
    {
        const cuuint64_t dims[3] = {64, (cuuint64_t)C, 6};
        const cuuint64_t str[2]  = {(cuuint64_t)C * 2, 128};
        const cuuint32_t box[3]  = {64, 32, 2};
        encode(fn, &tm_wl3, w_lat, 3, dims, str, box);
    }
    fpn_kernel<<<grid, NTHREADS, SMEM_BYTES>>>(scr, w_out, c_fine, p_coarse, (NSEG + grid / 2 - 1) / (grid / 2), 1.0f,
                                               tm_w64, tm_wl3, tm_p8, tm_c, tm_p, tm_out);
}
```

```cpp
#include <cuda_runtime.h>
#include <cuda_bf16.h>
#include <cuda.h>
#include <stdint.h>

namespace {

constexpr int C          = 384;
constexpr int HW         = 384;
constexpr int NPIX       = HW * HW;
constexpr int NSEG       = NPIX / 64;
constexpr int NJOBS      = 36;

constexpr int NSLOTS     = 10;
constexpr int NPAIRS     = 64;
constexpr int PF_LEAD    = 5;
constexpr int PF_LEAD0   = 17;
constexpr int PF_DECAY   = 8;
constexpr int PF_START   = 3;
constexpr int PF_FIRST   = 9;
constexpr int PF_GAP     = 50;
constexpr int PF_GAP0    = 150;
constexpr int GOV_START  = 18;
constexpr int EF_STEPS   = 10;
constexpr int CLR_AT     = 20;

constexpr int SLOT_BYTES  = 8192;
constexpr int WOUT_SLICE  = 320 * 128;
constexpr int OFF_WOUT    = 0;
constexpr int OFF_RING    = 3 * WOUT_SLICE;
constexpr int OFF_STAGE   = OFF_RING + NSLOTS * SLOT_BYTES;
constexpr int OFF_FULL    = OFF_STAGE + 3 * 8192;
constexpr int OFF_EMPTY   = OFF_FULL + 8 * NSLOTS;
constexpr int OFF_JB2     = OFF_EMPTY + 8 * NSLOTS;
constexpr int OFF_PACE    = OFF_JB2 + 8;
constexpr int SMEM_BYTES  = OFF_PACE + 8;
static_assert(SMEM_BYTES <= 232448, "smem");
static_assert(NSLOTS >= 10, "the first tile (nine ring items) is requested in the prologue");

constexpr int NTHREADS = 512;
constexpr uint64_t POLICY_EVICT_FIRST  = 0x12F0000000000000ull;
constexpr uint64_t POLICY_EVICT_NORMAL = 0x1000000000000000ull;

struct Scratch {
    uint4    wfrag[2 * 6 * 24 * 128];
    unsigned epoch;
    unsigned pad0[31];
    unsigned prog;
};
__device__ Scratch g_scratch;

__device__ __forceinline__ uint32_t smem_u32(const void* p) { return (uint32_t)__cvta_generic_to_shared(p); }

__device__ __forceinline__ void mbar_init(uint32_t bar, uint32_t cnt) {
    asm volatile("mbarrier.init.shared::cta.b64 [%0], %1;" ::"r"(bar), "r"(cnt) : "memory");
}
__device__ __forceinline__ void mbar_expect_tx(uint32_t bar, uint32_t bytes) {
    asm volatile("mbarrier.arrive.expect_tx.shared::cta.b64 _, [%0], %1;" ::"r"(bar), "r"(bytes) : "memory");
}
__device__ __forceinline__ void mbar_wait_bounded(uint32_t bar, uint32_t parity) {
    asm volatile(
        "{\n"
        ".reg .pred p;\n"
        ".reg .u32 n;\n"
        "mbarrier.try_wait.parity.shared::cta.b64 p, [%0], %1;\n"
        "@p bra DONE_%=;\n"
        "mov.u32 n, 0;\n"
        "WAIT_%=:\n"
        "mbarrier.try_wait.parity.shared::cta.b64 p, [%0], %1;\n"
        "@p bra DONE_%=;\n"
        "add.u32 n, n, 1;\n"
        "setp.lt.u32 p, n, 4000000;\n"
        "@p bra WAIT_%=;\n"
        "trap;\n"
        "DONE_%=:\n"
        "}\n" ::"r"(bar), "r"(parity) : "memory");
}
__device__ __forceinline__ void mbar_wait(uint32_t bar, uint32_t parity) {
    asm volatile(
        "{\n"
        ".reg .pred p;\n"
        "WAIT_%=:\n"
        "mbarrier.try_wait.parity.shared::cta.b64 p, [%0], %1;\n"
        "@!p bra WAIT_%=;\n"
        "}\n" ::"r"(bar), "r"(parity) : "memory");
}
__device__ __forceinline__ bool mbar_try(uint32_t bar, uint32_t parity) {
    uint32_t r;
    asm volatile("{\n.reg .pred p;\nmbarrier.test_wait.parity.shared::cta.b64 p, [%1], %2;\nselp.u32 %0, 1, 0, p;\n}\n"
                 : "=r"(r) : "r"(bar), "r"(parity) : "memory");
    return r != 0;
}
__device__ __forceinline__ void mbar_arrive_cluster(uint32_t cluster_addr) {
    asm volatile("mbarrier.arrive.shared::cluster.b64 _, [%0];" ::"r"(cluster_addr) : "memory");
}
__device__ __forceinline__ uint32_t mapa(uint32_t addr, uint32_t rank) {
    uint32_t r;
    asm("mapa.shared::cluster.u32 %0, %1, %2;" : "=r"(r) : "r"(addr), "r"(rank));
    return r;
}
__device__ __forceinline__ void named_bar(int wg) {
    asm volatile("bar.sync %0, 128;" ::"r"(wg + 1) : "memory");
}

__device__ __forceinline__ void tma_load_2d(uint32_t dst, const CUtensorMap* tm, int c0, int c1, uint32_t bar) {
    asm volatile("cp.async.bulk.tensor.2d.shared::cluster.global.mbarrier::complete_tx::bytes [%0], [%1, {%2, %3}], [%4];"
                 ::"r"(dst), "l"(tm), "r"(c0), "r"(c1), "r"(bar) : "memory");
}
__device__ __forceinline__ void tma_load_3d(uint32_t dst, const CUtensorMap* tm, int c0, int c1, int c2, uint32_t bar) {
    asm volatile("cp.async.bulk.tensor.3d.shared::cluster.global.mbarrier::complete_tx::bytes [%0], [%1, {%2, %3, %4}], [%5];"
                 ::"r"(dst), "l"(tm), "r"(c0), "r"(c1), "r"(c2), "r"(bar) : "memory");
}
__device__ __forceinline__ void tma_load_5d(uint32_t dst, const CUtensorMap* tm, int c0, int c3, int c4, uint32_t bar) {
    asm volatile("cp.async.bulk.tensor.5d.shared::cluster.global.mbarrier::complete_tx::bytes [%0], [%1, {%2, 0, 0, %3, %4}], [%5];"
                 ::"r"(dst), "l"(tm), "r"(c0), "r"(c3), "r"(c4), "r"(bar) : "memory");
}
__device__ __forceinline__ void tma_load_2d_mc(uint32_t dst, const CUtensorMap* tm, int c0, int c1, uint32_t bar, uint64_t pol) {
    asm volatile("cp.async.bulk.tensor.2d.shared::cluster.global.mbarrier::complete_tx::bytes.multicast::cluster.L2::cache_hint"
                 " [%0], [%1, {%2, %3}], [%4], %5, %6;"
                 ::"r"(dst), "l"(tm), "r"(c0), "r"(c1), "r"(bar), "h"((uint16_t)3), "l"(pol) : "memory");
}
__device__ __forceinline__ void tma_load_5d_mc(uint32_t dst, const CUtensorMap* tm, int c0, int c3, int c4, uint32_t bar, uint64_t pol) {
    asm volatile("cp.async.bulk.tensor.5d.shared::cluster.global.mbarrier::complete_tx::bytes.multicast::cluster.L2::cache_hint"
                 " [%0], [%1, {%2, 0, 0, %3, %4}], [%5], %6, %7;"
                 ::"r"(dst), "l"(tm), "r"(c0), "r"(c3), "r"(c4), "r"(bar), "h"((uint16_t)3), "l"(pol) : "memory");
}
__device__ __forceinline__ void tma_store_2d(const CUtensorMap* tm, int c0, int c1, uint32_t src, uint64_t pol) {
    asm volatile("cp.async.bulk.tensor.2d.global.shared::cta.bulk_group.L2::cache_hint [%0, {%1, %2}], [%3], %4;"
                 ::"l"(tm), "r"(c0), "r"(c1), "r"(src), "l"(pol) : "memory");
}
__device__ __forceinline__ void prefetch_tmap(const CUtensorMap* tm) {
    asm volatile("prefetch.tensormap [%0];" ::"l"(tm) : "memory");
}

__device__ __forceinline__ void wg_fence()  { asm volatile("wgmma.fence.sync.aligned;" ::: "memory"); }
__device__ __forceinline__ void wg_commit() { asm volatile("wgmma.commit_group.sync.aligned;" ::: "memory"); }
template <int N> __device__ __forceinline__ void wg_wait() { asm volatile("wgmma.wait_group.sync.aligned %0;" ::"n"(N) : "memory"); }

#define ACC16(a)                                                                                              \
    "+f"(a[0]), "+f"(a[1]), "+f"(a[2]), "+f"(a[3]), "+f"(a[4]), "+f"(a[5]), "+f"(a[6]), "+f"(a[7]),           \
    "+f"(a[8]), "+f"(a[9]), "+f"(a[10]), "+f"(a[11]), "+f"(a[12]), "+f"(a[13]), "+f"(a[14]), "+f"(a[15])
#define ACC32(a)                                                                                              \
    ACC16(a),                                                                                                 \
    "+f"(a[16]), "+f"(a[17]), "+f"(a[18]), "+f"(a[19]), "+f"(a[20]), "+f"(a[21]), "+f"(a[22]), "+f"(a[23]),   \
    "+f"(a[24]), "+f"(a[25]), "+f"(a[26]), "+f"(a[27]), "+f"(a[28]), "+f"(a[29]), "+f"(a[30]), "+f"(a[31])
#define ACC16_STR "{%0, %1, %2, %3, %4, %5, %6, %7, %8, %9, %10, %11, %12, %13, %14, %15}"
#define ACC32_STR                                                                                             \
    "{%0, %1, %2, %3, %4, %5, %6, %7, %8, %9, %10, %11, %12, %13, %14, %15, "                                 \
    "%16, %17, %18, %19, %20, %21, %22, %23, %24, %25, %26, %27, %28, %29, %30, %31}"

template <int BOFF>
__device__ __forceinline__ void wgmma_rs(float (&d)[32], uint32_t a0, uint32_t a1, uint32_t a2, uint32_t a3, uint32_t db_lo) {
    asm volatile("{\n.reg .b64 db;\n.reg .b32 lo;\n"
                 "add.u32 lo, %36, %37;\nmov.b64 db, {lo, 0x40000040};\n"
                 "wgmma.mma_async.sync.aligned.m64n64k16.f32.bf16.bf16 " ACC32_STR
                 ", {%32, %33, %34, %35}, db, 1, -1, 1, 0;\n}"
                 : ACC32(d) : "r"(a0), "r"(a1), "r"(a2), "r"(a3), "r"(db_lo), "n"(BOFF));
}
template <int ACCUM, int AOFF, int BOFF>
__device__ __forceinline__ void wgmma_ss(float (&d)[32], uint32_t da_lo, uint32_t db_lo) {
    asm volatile("{\n.reg .b64 da, db;\n.reg .b32 lo;\n"
                 "add.u32 lo, %32, %35;\nmov.b64 da, {lo, 0x40000040};\n"
                 "add.u32 lo, %33, %36;\nmov.b64 db, {lo, 0x40000040};\n"
                 "wgmma.mma_async.sync.aligned.m64n64k16.f32.bf16.bf16 " ACC32_STR
                 ", da, db, %34, 1, 1, 1, 0;\n}"
                 : ACC32(d) : "r"(da_lo), "r"(db_lo), "n"(ACCUM), "n"(AOFF), "n"(BOFF));
}
template <int ACCUM, int AOFF, int BOFF>
__device__ __forceinline__ void wgmma_ss32(float (&d)[16], uint32_t da_lo, uint32_t db_lo) {
    asm volatile("{\n.reg .b64 da, db;\n.reg .b32 lo;\n"
                 "add.u32 lo, %16, %19;\nmov.b64 da, {lo, 0x40000040};\n"
                 "add.u32 lo, %17, %20;\nmov.b64 db, {lo, 0x40000040};\n"
                 "wgmma.mma_async.sync.aligned.m64n32k16.f32.bf16.bf16 " ACC16_STR
                 ", da, db, %18, 1, 1, 1, 0;\n}"
                 : ACC16(d) : "r"(da_lo), "r"(db_lo), "n"(ACCUM), "n"(AOFF), "n"(BOFF));
}
__device__ __forceinline__ uint32_t desc_lo(uint32_t addr) { return ((addr & 0x3FFFFu) >> 4) | (1u << 16); }
__device__ __forceinline__ uint32_t pack_bf16(float lo, float hi) {
    uint32_t r;
    asm("cvt.rn.bf16x2.f32 %0, %1, %2;" : "=r"(r) : "f"(hi), "f"(lo));
    return r;
}
__device__ __forceinline__ uint32_t pack_neg(float lo, float hi) {
    const uint32_t v = pack_bf16(lo, hi) ^ 0x80008000u;
    return v == 0u ? 0x80008000u : v;
}
__device__ __forceinline__ float dup(float x, float one) {
    float r;
    asm volatile("mul.f32 %0, %1, %2;" : "=f"(r) : "f"(x), "f"(one));
    return r;
}
__device__ __forceinline__ void stsm_x4_t(uint32_t addr, uint32_t r0, uint32_t r1, uint32_t r2, uint32_t r3) {
    asm volatile("stmatrix.sync.aligned.m8n8.x4.trans.shared.b16 [%0], {%1, %2, %3, %4};"
                 ::"r"(addr), "r"(r0), "r"(r1), "r"(r2), "r"(r3) : "memory");
}

struct Ring {
    uint32_t so;
    uint32_t ph;
    __device__ __forceinline__ void advance() {
        so += 8;
        if (so == NSLOTS * 8) { so = 0; ph ^= 1; }
    }
    __device__ __forceinline__ uint32_t prev() const { return so == 0 ? (NSLOTS - 1) * 8 : so - 8; }
    __device__ __forceinline__ uint32_t back(uint32_t k) const { return so >= k * 8 ? so - k * 8 : so + (NSLOTS - k) * 8; }
};

struct Ctx {
    uint32_t sbase;
    uint32_t db0;
    uint32_t empty_tgt;
    bool     signal;
};

template <int KC, bool RS>
__device__ __forceinline__ void chunk(float (&acc)[32], const uint32_t (&W)[96], uint32_t da0, const Ctx& cx, Ring& rg, bool& ready) {
    if (!ready) mbar_wait(cx.sbase + OFF_FULL + rg.so, rg.ph);
    const uint32_t db = cx.db0 + rg.so * 64;
    const uint32_t prev = rg.prev();
    rg.advance();
    ready = mbar_try(cx.sbase + OFF_FULL + rg.so, rg.ph);
    wg_fence();
    if (RS) {
        wgmma_rs<0>(acc, W[KC * 16 + 0],  W[KC * 16 + 1],  W[KC * 16 + 2],  W[KC * 16 + 3],  db);
        wgmma_rs<2>(acc, W[KC * 16 + 4],  W[KC * 16 + 5],  W[KC * 16 + 6],  W[KC * 16 + 7],  db);
        wgmma_rs<4>(acc, W[KC * 16 + 8],  W[KC * 16 + 9],  W[KC * 16 + 10], W[KC * 16 + 11], db);
        wgmma_rs<6>(acc, W[KC * 16 + 12], W[KC * 16 + 13], W[KC * 16 + 14], W[KC * 16 + 15], db);
    } else {
        wgmma_ss<(KC > 0), (KC * 4 + 0) * 128, 0>(acc, da0, db);
        wgmma_ss<1,        (KC * 4 + 1) * 128, 2>(acc, da0, db);
        wgmma_ss<1,        (KC * 4 + 2) * 128, 4>(acc, da0, db);
        wgmma_ss<1,        (KC * 4 + 3) * 128, 6>(acc, da0, db);
    }
    wg_commit();
    if (KC > 0) {
        wg_wait<1>();
        if (cx.signal) mbar_arrive_cluster(cx.empty_tgt + prev);
    }
}

__device__ __forceinline__ void chunk_q5(float (&acc)[32], int wg, const Ctx& cx, Ring& rg, bool& ready) {
    Ring r = rg;
    const uint32_t db = cx.db0 + r.so * 64;
    uint32_t da = 0;
    bool ok = ready;
#pragma unroll
    for (int g = 0; g < 3; g++) {
        r.advance();
        ok = mbar_try(cx.sbase + OFF_FULL + r.so, r.ph) && ok;
        if (g == wg) da = cx.db0 + r.so * 64;
    }
    if (!ok) {
        Ring t = rg;
#pragma unroll 1
        for (int g = 0; g < 4; g++) {
            mbar_wait(cx.sbase + OFF_FULL + t.so, t.ph);
            t.advance();
        }
    }
    r.advance();
    ready = mbar_try(cx.sbase + OFF_FULL + r.so, r.ph);
    wg_fence();
    wgmma_ss<1, 0 * 128, 0>(acc, da, db);
    wgmma_ss<1, 1 * 128, 2>(acc, da, db);
    wgmma_ss<1, 2 * 128, 4>(acc, da, db);
    wgmma_ss<1, 3 * 128, 6>(acc, da, db);
    wg_commit();
    wg_wait<1>();
    if (cx.signal) mbar_arrive_cluster(cx.empty_tgt + rg.prev());
    rg = r;
}
__device__ __forceinline__ void finish_q(const Ctx& cx, const Ring& rg) {
    wg_wait<0>();
    if (cx.signal) {
        mbar_arrive_cluster(cx.empty_tgt + rg.back(4));
        mbar_arrive_cluster(cx.empty_tgt + rg.back(3));
        mbar_arrive_cluster(cx.empty_tgt + rg.back(2));
        mbar_arrive_cluster(cx.empty_tgt + rg.back(1));
    }
}

__device__ __forceinline__ int seg_row(int g) {
    const int y = g / 12;
    return y * (2 * HW) + (g - y * 12) * 32;
}

template <int NP>
__global__ void __cluster_dims__(2, 1, 1) __launch_bounds__(NTHREADS, 1)
fpn_kernel(Scratch* scr, const __nv_bfloat16* __restrict__ wo_ptr,
           const __nv_bfloat16* __restrict__ c_ptr, const __nv_bfloat16* __restrict__ p_ptr, const int nsteps, const float one,
           const __grid_constant__ CUtensorMap tm_w64, const __grid_constant__ CUtensorMap tm_wl3,
           const __grid_constant__ CUtensorMap tm_p8, const __grid_constant__ CUtensorMap tm_c,
           const __grid_constant__ CUtensorMap tm_p, const __grid_constant__ CUtensorMap tm_out)
{
    extern __shared__ __align__(1024) uint8_t smem[];
    const uint32_t sbase = smem_u32(smem);
    const int tid   = threadIdx.x;
    const int warp  = __shfl_sync(0xffffffffu, tid >> 5, 0);
    const int lane  = tid & 31;
    const int rank  = blockIdx.x & 1;
    const int pair  = blockIdx.x >> 1;
    const int npair = NP ? NP : gridDim.x >> 1;
    const int nfine = NP ? NSEG / (NP ? NP : 1) : nsteps;

    if (tid == 480) {
        prefetch_tmap(&tm_w64); prefetch_tmap(&tm_wl3); prefetch_tmap(&tm_p8);
        prefetch_tmap(&tm_c); prefetch_tmap(&tm_p); prefetch_tmap(&tm_out);
    }
    if (tid == 384) {
        for (int s = 0; s < 3; s++) mbar_init(sbase + OFF_FULL + s * 8, 1);
        asm volatile("fence.mbarrier_init.release.cluster;" ::: "memory");
        asm volatile("fence.proxy.async.shared::cta;" ::: "memory");
        const int g0 = pair % 3;
#pragma unroll 1
        for (int s = 0; s < 3; s++) {
            const uint32_t bar = sbase + OFF_FULL + s * 8;
            const uint32_t dst = sbase + OFF_WOUT + g0 * WOUT_SLICE + s * 16384;
            mbar_expect_tx(bar, pair < NJOBS ? 3 * SLOT_BYTES : 2 * SLOT_BYTES);
            tma_load_2d(dst, &tm_w64, rank * 192 + g0 * 64, s * 128, bar);
            if (pair < NJOBS) tma_load_3d(sbase + OFF_RING + s * SLOT_BYTES, &tm_wl3, 0, (pair / 3) * 32, 2 * s, bar);
            tma_load_2d(s < 2 ? dst + 8192 : sbase + OFF_STAGE + g0 * 8192, &tm_w64, rank * 192 + g0 * 64, s * 128 + 64, bar);
        }
    }
    if (warp == 13) {
        if (lane == 0) {
            for (int s = 0; s < NSLOTS; s++) {
                if (s >= 3) mbar_init(sbase + OFF_FULL + s * 8, 1);
                mbar_init(sbase + OFF_EMPTY + s * 8, 6);
            }
            mbar_init(sbase + OFF_JB2, 1);
            asm volatile("st.volatile.shared.u32 [%0], %1;" ::"r"(sbase + OFF_PACE), "r"(6) : "memory");
            asm volatile("fence.mbarrier_init.release.cluster;" ::: "memory");
            asm volatile("fence.proxy.async.shared::cta;" ::: "memory");
        }
        __syncwarp();
        asm volatile("bar.arrive 5, 448;" ::: "memory");
    }
    __syncwarp();
    asm volatile("barrier.cluster.arrive.relaxed.aligned;" ::: "memory");

    if (warp >= 12) {
        asm volatile("setmaxnreg.dec.sync.aligned.u32 32;");
        if (warp == 12) {
            asm volatile("bar.sync 5, 448;" ::: "memory");
            if (lane == 0) {
                const int g1 = (pair + 1) % 3, g2 = (pair + 2) % 3;
#pragma unroll 1
                for (int kc = 0; kc < 6; kc++) {
                    const uint32_t bar = sbase + OFF_FULL + (3 + kc) * 8;
                    mbar_expect_tx(bar, 3 * SLOT_BYTES);
                    tma_load_5d(sbase + OFF_RING + (3 + kc) * SLOT_BYTES, &tm_p8, kc * 64, pair * 2, 0, bar);
                    tma_load_2d(kc < 5 ? sbase + OFF_WOUT + g1 * WOUT_SLICE + kc * 8192 : sbase + OFF_STAGE + g1 * 8192,
                                &tm_w64, rank * 192 + g1 * 64, kc * 64, bar);
                    tma_load_2d(kc < 5 ? sbase + OFF_WOUT + g2 * WOUT_SLICE + kc * 8192 : sbase + OFF_STAGE + g2 * 8192,
                                &tm_w64, rank * 192 + g2 * 64, kc * 64, bar);
                }
            }
            __syncwarp();
        }
        asm volatile("barrier.cluster.wait.aligned;" ::: "memory");
        if (warp == 12) {
            if (lane == 0) {
                const uint32_t dst0 = sbase + OFF_RING + rank * 4096;
                uint32_t so = 9 * 8, ph = 1, step = 6;
                auto acquire = [&](uint32_t& bar, uint32_t& dst) {
                    bar = sbase + OFF_FULL + so;
                    dst = dst0 + so * (SLOT_BYTES / 8);
                    mbar_wait_bounded(sbase + OFF_EMPTY + so, ph);
                    mbar_expect_tx(bar, SLOT_BYTES);
                };
                auto next_slot = [&]() {
                    so += 8;
                    if (so == NSLOTS * 8) { so = 0; ph ^= 1; }
                };
                auto advance = [&]() {
                    next_slot();
                    step++;
                    asm volatile("st.volatile.shared.u32 [%0], %1;" ::"r"(sbase + OFF_PACE), "r"(step) : "memory");
                };
                unsigned mytiles = 0, seen = 0;
                auto look = [&]() {
                    asm volatile("ld.relaxed.gpu.global.u32 %0, [%1];" : "=r"(seen) : "l"(&scr->prog) : "memory");
                };
                auto count = [&]() {
                    asm volatile("red.relaxed.gpu.global.add.u32 [%0], 1;" ::"l"(&scr->prog) : "memory");
                };
                auto govern = [&]() {
                    if (rank == 0) {
                        unsigned spins = 0;
                        while (mytiles >= GOV_START && mytiles * npair > seen && ++spins < 100000u) look();
                        mytiles++;
                    }
                };
#pragma unroll 1
                for (int j = 0; j < nfine; j++) {
                    const uint64_t pol = j >= nfine - EF_STEPS ? POLICY_EVICT_FIRST : POLICY_EVICT_NORMAL;
                    if ((j & 3) == 0 && j > 0) {
                        govern();
#pragma unroll
                        for (int kc = 0; kc < 6; kc++) {
                            uint32_t bar, dst;
                            acquire(bar, dst);
                            tma_load_5d_mc(dst, &tm_p, kc * 64, pair * 2, j + 2 * rank, bar, pol);
                            advance();
                            if (kc == 0 && rank == 0) count();
                        }
#pragma unroll
                        for (int g = 0; g < 3; g++) {
                            uint32_t bar, dst;
                            acquire(bar, dst);
                            tma_load_2d(dst - rank * 4096, &tm_w64, rank * 192 + g * 64, 320, bar);
                            next_slot();
                            if (g == 0 && rank == 0) look();
                        }
                    }
                    const int row = seg_row(j * npair + pair) + rank * HW;
                    govern();
#pragma unroll
                    for (int kc = 0; kc < 6; kc++) {
                        uint32_t bar, dst;
                        acquire(bar, dst);
                        tma_load_2d_mc(dst, &tm_c, kc * 64, row, bar, pol);
                        advance();
                        if (kc == 0 && rank == 0 && j + 1 < nfine) count();
                        if (kc == 3 && rank == 0) look();
                    }
                }
                if (rank == 0) {
                    if (atomicAdd(&scr->prog, 1u) + 1 == mytiles * npair) {
                        asm volatile("st.relaxed.gpu.global.u32 [%0], 0;" ::"l"(&scr->prog) : "memory");
                        asm volatile("red.relaxed.gpu.global.add.u32 [%0], 1;" ::"l"(&scr->epoch) : "memory");
                    }
                }
                for (int s = 0; s < NSLOTS; s++) {
                    mbar_wait_bounded(sbase + OFF_EMPTY + so, ph);
                    next_slot();
                }
            }
        } else if (warp == 13) {
            uint32_t sink = 0, pv = 0;
#pragma unroll 1
            for (int i = PF_START; i < nfine + nfine / 4; i++) {
                const int k5 = i / 5, t = i - k5 * 5;
                const char *b0, *b1;
                if (t == 0) {
                    b0 = (const char*)p_ptr + (size_t)((4 * k5 + 2 * rank) * npair + pair) * (16 * C * 2);
                    b1 = b0 + (size_t)npair * (16 * C * 2);
                } else {
                    b0 = (const char*)c_ptr + (size_t)(seg_row((4 * k5 + t - 1) * npair + pair) + rank * HW) * (C * 2);
                    b1 = b0 + 16 * C * 2;
                }
                const int need = max(6 * i - max(PF_LEAD0 - max(i - PF_DECAY, 0), PF_LEAD), PF_FIRST);
                unsigned spins = 0;
                while (true) {
                    uint32_t v;
                    asm volatile("ld.volatile.shared.u32 %0, [%1];" : "=r"(v) : "r"(sbase + OFF_PACE) : "memory");
                    if ((int)v >= need || ++spins > 4000000u) break;
                    __nanosleep(20);
                }
#pragma unroll
                for (int k = 0; k < 6; k++) {
                    asm volatile("prefetch.global.L2 [%0];" ::"l"((k < 3 ? b0 : b1) + lane * 128 + (k % 3) * 4096) : "memory");
                    __nanosleep(i < PF_START + 2 ? PF_GAP0 : PF_GAP);
                }
                if ((t == 0 || t == 3) && i > 5) {
                    const int idx = ((pair + i * 5) % 6) * 32 + lane;
                    sink ^= pv;
                    asm volatile("ld.global.cg.u32 %0, [%1];" : "=r"(pv)
                                 : "l"((const char*)wo_ptr + (320 + idx / 3) * (C * 2) + rank * 384 + (idx % 3) * 128) : "memory");
                }
            }
            asm volatile("st.volatile.shared.u32 [%0], %1;" ::"r"(sbase + OFF_PACE + 4), "r"(sink ^ pv) : "memory");
        } else if (warp == 15) {
            uint32_t par, v;
            asm volatile("ld.relaxed.gpu.global.u32 %0, [%1];" : "=r"(par) : "l"(&scr->epoch) : "memory");
            uint4* clr = scr->wfrag + (~par & 1) * (6 * 24 * 128);
            unsigned spins = 0;
            do {
                __nanosleep(500);
                asm volatile("ld.volatile.shared.u32 %0, [%1];" : "=r"(v) : "r"(sbase + OFF_PACE) : "memory");
            } while (v < CLR_AT && ++spins < 100000u);
            for (int i = blockIdx.x * 32 + lane; i < 6 * 24 * 128; i += npair * 64) clr[i] = make_uint4(0u, 0u, 0u, 0u);
        }
    } else {
        uint32_t par;
        asm volatile("ld.relaxed.gpu.global.u32 %0, [%1];" : "=r"(par) : "l"(&scr->epoch) : "memory");
        asm volatile("setmaxnreg.inc.sync.aligned.u32 160;");
        asm volatile("bar.sync 5, 448;" ::: "memory");
        const int wg   = warp >> 2;
        const int wtid = tid & 127;
        Ctx cx;
        cx.sbase     = sbase;
        cx.db0       = desc_lo(sbase + OFF_RING);
        cx.empty_tgt = mapa(sbase + OFF_EMPTY, warp & 1);
        cx.signal    = (lane == 0) && ((warp & 3) < 2);
        const uint32_t da0 = desc_lo(sbase + OFF_WOUT + wg * WOUT_SLICE);
        const int cb = rank * 3 + wg;

        float    acc[32];
        uint32_t qp[16];
        uint32_t W[96];
        Ring rg{0u, 0u};

        const uint32_t da5 = desc_lo(sbase + OFF_STAGE + wg * 8192) - 20 * 128;

        {
            uint32_t jph = 0;
            for (int job = pair; job < NJOBS; job += npair) {
                if (job % 3 == wg) {
                    if (job != pair) {
                        named_bar(wg);
                        if (wtid == 0) {
                            mbar_expect_tx(sbase + OFF_JB2, 6 * 4096);
                            for (int s = 0; s < 3; s++)
                                tma_load_3d(sbase + OFF_RING + s * SLOT_BYTES, &tm_wl3, 0, (job / 3) * 32, 2 * s, sbase + OFF_JB2);
                        }
                        for (int kc = 0; kc < 6; kc++) mbar_wait(sbase + OFF_FULL + (3 + kc) * 8, 0);
                        mbar_wait(sbase + OFF_JB2, jph);
                    }
                    float ja[16];
#define JOBK(k) wgmma_ss32<((k) > 0), (k) * 128, ((k) >> 2) * 256 + ((k) & 3) * 2>(ja, (k) < 20 ? da0 : da5, cx.db0);
                    mbar_wait(sbase + OFF_FULL, 0);
                    wg_fence();
                    JOBK(0)  JOBK(1)  JOBK(2)  JOBK(3)  JOBK(4)  JOBK(5)  JOBK(6)  JOBK(7)
                    wg_commit();
                    mbar_wait(sbase + OFF_FULL + 8, 0);
                    wg_fence();
                    JOBK(8)  JOBK(9)  JOBK(10) JOBK(11) JOBK(12) JOBK(13) JOBK(14) JOBK(15)
                    wg_commit();
                    mbar_wait(sbase + OFF_FULL + 16, 0);
                    wg_fence();
                    JOBK(16) JOBK(17) JOBK(18) JOBK(19) JOBK(20) JOBK(21) JOBK(22) JOBK(23)
#undef JOBK
                    wg_commit();
                    wg_wait<0>();
                    const int fidx = (cb * 24 + (job / 3) * 2) * 128 + wtid;
                    uint4* dst = scr->wfrag + (par & 1) * (6 * 24 * 128) + fidx;
#pragma unroll
                    for (int i = 0; i < 2; i++) {
                        asm volatile("st.relaxed.gpu.global.v4.u32 [%0], {%1, %2, %3, %4};" ::"l"(dst + i * 128),
                                     "r"(pack_neg(ja[8 * i + 0], ja[8 * i + 1])), "r"(pack_neg(ja[8 * i + 2], ja[8 * i + 3])),
                                     "r"(pack_neg(ja[8 * i + 4], ja[8 * i + 5])), "r"(pack_neg(ja[8 * i + 6], ja[8 * i + 7])) : "memory");
                    }
                }
                if (job + npair < NJOBS) asm volatile("bar.sync 4, 384;" ::: "memory");
                if (job != pair) jph ^= 1;
            }
        }

        par &= 1;
        if (pair < NJOBS) asm volatile("bar.sync 6, 384;" ::: "memory");
        asm volatile("barrier.cluster.wait.aligned;" ::: "memory");

        mbar_wait(sbase + OFF_FULL, 0);
        mbar_wait(sbase + OFF_FULL + 8, 0);
        mbar_wait(sbase + OFF_FULL + 16, 0);
        if (cx.signal) {
            mbar_arrive_cluster(cx.empty_tgt);
            mbar_arrive_cluster(cx.empty_tgt + 8);
            mbar_arrive_cluster(cx.empty_tgt + 16);
        }
        rg.so = 3 * 8;
        bool ready = false;

        const uint4* wsrc = scr->wfrag + (par * 6 + cb) * (24 * 128) + wtid;
        auto load_w = [&](int kc) {
#pragma unroll
            for (int s = 4 * kc; s < 4 * kc + 4; s++) {
                asm volatile("ld.relaxed.gpu.global.v4.u32 {%0, %1, %2, %3}, [%4];"
                             : "=r"(W[4 * s]), "=r"(W[4 * s + 1]), "=r"(W[4 * s + 2]), "=r"(W[4 * s + 3])
                             : "l"(wsrc + s * 128) : "memory");
            }
        };
        auto check_w = [&](int kc) {
            uint32_t* w = W + 16 * kc;
            asm volatile(
                "{\n.reg .pred p;\n.reg .u32 m, n;\n"
                "mov.u32 n, 0;\n"
                "CHK_%=:\n"
                "mov.u32 m, %%clock;\n or.b32 m, m, 1;\n min.u32 m, m, %0;\n"
                "min.u32 m, m, %1;\n min.u32 m, m, %2;\n min.u32 m, m, %3;\n min.u32 m, m, %4;\n min.u32 m, m, %5;\n"
                "min.u32 m, m, %6;\n min.u32 m, m, %7;\n min.u32 m, m, %8;\n min.u32 m, m, %9;\n min.u32 m, m, %10;\n"
                "min.u32 m, m, %11;\n min.u32 m, m, %12;\n min.u32 m, m, %13;\n min.u32 m, m, %14;\n min.u32 m, m, %15;\n"
                "setp.ne.u32 p, m, 0;\n"
                "vote.sync.all.pred p, p, 0xffffffff;\n"
                "@p bra.uni OK_%=;\n"
                "add.u32 n, n, 1;\n"
                "setp.gt.u32 p, n, 5000000;\n"
                "@p bra.uni OK_%=;\n"
                "ld.relaxed.gpu.global.v4.u32 {%0, %1, %2, %3}, [%16];\n"
                "ld.relaxed.gpu.global.v4.u32 {%4, %5, %6, %7}, [%16 + 2048];\n"
                "ld.relaxed.gpu.global.v4.u32 {%8, %9, %10, %11}, [%16 + 4096];\n"
                "ld.relaxed.gpu.global.v4.u32 {%12, %13, %14, %15}, [%16 + 6144];\n"
                "bra.uni CHK_%=;\n"
                "OK_%=:\n}"
                : "+r"(w[0]), "+r"(w[1]), "+r"(w[2]), "+r"(w[3]), "+r"(w[4]), "+r"(w[5]), "+r"(w[6]), "+r"(w[7]),
                  "+r"(w[8]), "+r"(w[9]), "+r"(w[10]), "+r"(w[11]), "+r"(w[12]), "+r"(w[13]), "+r"(w[14]), "+r"(w[15])
                : "l"(wsrc + kc * 512) : "memory");
        };
        chunk<0, false>(acc, W, da0, cx, rg, ready);
        chunk<1, false>(acc, W, da0, cx, rg, ready);
        chunk<2, false>(acc, W, da0, cx, rg, ready);
        load_w(0);
        chunk<3, false>(acc, W, da0, cx, rg, ready);
        load_w(1);
        chunk<4, false>(acc, W, da0, cx, rg, ready);
        load_w(2);
        chunk<5, false>(acc, W, da5, cx, rg, ready);
        wg_wait<0>();
        if (cx.signal) mbar_arrive_cluster(cx.empty_tgt + rg.prev());
#pragma unroll
        for (int i = 0; i < 16; i++) qp[i] = pack_bf16(acc[2 * i], acc[2 * i + 1]);

        const uint32_t stage = sbase + OFF_STAGE + wg * 8192;
        const uint32_t st_addr = stage + (((lane >> 4) * 8 + (lane & 7)) << 7)
                               + (((((warp & 3) << 1) | ((lane >> 3) & 1)) ^ (lane & 7)) << 4);
        auto flush_part = [&](int row, int part) {
            if (part == 0) {
                asm volatile("fence.proxy.async.shared::cta;" ::: "memory");
                named_bar(wg);
            }
            if (wtid == 0) {
                tma_store_2d(&tm_out, cb * 64, row + (part >> 1) * HW + (part & 1) * 16, stage + part * 2048, POLICY_EVICT_FIRST);
                if (part == 3) asm volatile("cp.async.bulk.commit_group;" ::: "memory");
            }
        };
        auto init_acc = [&]() {
#pragma unroll
            for (int b = 0; b < 2; b++) {
#pragma unroll
                for (int h = 0; h < 2; h++) {
                    const uint32_t q = qp[b * 2 + h];
                    const float lo = __uint_as_float(q << 16), hi = __uint_as_float(q & 0xffff0000u);
#pragma unroll
                    for (int dy = 0; dy < 2; dy++) {
                        acc[16 * dy + 8 * b + 2 * h]         = dy ? dup(lo, one) : lo;
                        acc[16 * dy + 8 * b + 2 * h + 1]     = dup(lo, one);
                        acc[16 * dy + 8 * b + 4 + 2 * h]     = dy ? dup(hi, one) : hi;
                        acc[16 * dy + 8 * b + 4 + 2 * h + 1] = dup(hi, one);
                    }
                }
            }
#pragma unroll
            for (int i = 0; i < 12; i++) qp[i] = qp[i + 4];
        };
        auto stage_tile = [&]() {
            wg_wait<0>();
            if (cx.signal) mbar_arrive_cluster(cx.empty_tgt + rg.prev());
#pragma unroll
            for (int i = 0; i < 8; i += 2) {
                stsm_x4_t(st_addr + i * 1024,
                          pack_bf16(acc[4 * i + 0], acc[4 * i + 1]), pack_bf16(acc[4 * i + 2], acc[4 * i + 3]),
                          pack_bf16(acc[4 * i + 4], acc[4 * i + 5]), pack_bf16(acc[4 * i + 6], acc[4 * i + 7]));
            }
        };

        init_acc();
        check_w(0);
        load_w(3);
        load_w(4);
        chunk<0, true>(acc, W, da0, cx, rg, ready);
        check_w(1);
        chunk<1, true>(acc, W, da0, cx, rg, ready);
        check_w(2);
        chunk<2, true>(acc, W, da0, cx, rg, ready);
        check_w(3);
        load_w(5);
        chunk<3, true>(acc, W, da0, cx, rg, ready);
        check_w(4);
        chunk<4, true>(acc, W, da0, cx, rg, ready);
        check_w(5);
        chunk<5, true>(acc, W, da0, cx, rg, ready);

        int prow = seg_row(pair);
        int j = 1;
        while (true) {
            if (wtid == 0) asm volatile("cp.async.bulk.wait_group.read 0;" ::: "memory");
            named_bar(wg);
            if (j >= nfine) break;
            const bool pend = (j & 3) != 0;
            if (pend) {
                stage_tile();
                init_acc();
                chunk<0, true>(acc, W, da0, cx, rg, ready);
                flush_part(prow, 0);
            } else {
                stage_tile();
                chunk<0, false>(acc, W, da0, cx, rg, ready);
                flush_part(prow, 0);
                chunk<1, false>(acc, W, da0, cx, rg, ready);
                chunk<2, false>(acc, W, da0, cx, rg, ready);
                flush_part(prow, 1);
                chunk<3, false>(acc, W, da0, cx, rg, ready);
                chunk<4, false>(acc, W, da0, cx, rg, ready);
                flush_part(prow, 2);
                chunk_q5(acc, wg, cx, rg, ready);
                flush_part(prow, 3);
                finish_q(cx, rg);
#pragma unroll
                for (int i = 0; i < 16; i++) qp[i] = pack_bf16(acc[2 * i], acc[2 * i + 1]);
                init_acc();
                chunk<0, true>(acc, W, da0, cx, rg, ready);
            }
            chunk<1, true>(acc, W, da0, cx, rg, ready);
            chunk<2, true>(acc, W, da0, cx, rg, ready);
            chunk<3, true>(acc, W, da0, cx, rg, ready);
            if (pend) { flush_part(prow, 1); flush_part(prow, 2); }
            chunk<4, true>(acc, W, da0, cx, rg, ready);
            if (pend) flush_part(prow, 3);
            chunk<5, true>(acc, W, da0, cx, rg, ready);
            prow = seg_row(j * npair + pair);
            j++;
        }
        stage_tile();
#pragma unroll
        for (int part = 0; part < 4; part++) flush_part(prow, part);
        if (wtid == 0) asm volatile("cp.async.bulk.wait_group.read 0;" ::: "memory");
    }
}

typedef CUresult (*EncodeFn)(CUtensorMap*, CUtensorMapDataType, cuuint32_t, void*, const cuuint64_t*, const cuuint64_t*,
                             const cuuint32_t*, const cuuint32_t*, CUtensorMapInterleave, CUtensorMapSwizzle,
                             CUtensorMapL2promotion, CUtensorMapFloatOOBfill);

void encode(EncodeFn fn, CUtensorMap* tm, const void* ptr, int rank, const cuuint64_t* dims, const cuuint64_t* strides,
            const cuuint32_t* box) {
    const cuuint32_t es[5] = {1, 1, 1, 1, 1};
    fn(tm, CU_TENSOR_MAP_DATA_TYPE_BFLOAT16, (cuuint32_t)rank, const_cast<void*>(ptr), dims, strides, box, es,
       CU_TENSOR_MAP_INTERLEAVE_NONE, CU_TENSOR_MAP_SWIZZLE_128B, CU_TENSOR_MAP_L2_PROMOTION_NONE,
       CU_TENSOR_MAP_FLOAT_OOB_FILL_NONE);
}

}

extern "C" void kernel_launch(void* const* d_in, const int* in_sizes, int n_in, void* d_out, int out_size) {
    (void)in_sizes; (void)n_in; (void)out_size;
    const __nv_bfloat16* c_fine   = (const __nv_bfloat16*)d_in[0];
    const __nv_bfloat16* p_coarse = (const __nv_bfloat16*)d_in[1];
    const __nv_bfloat16* w_lat    = (const __nv_bfloat16*)d_in[2];
    const __nv_bfloat16* w_out    = (const __nv_bfloat16*)d_in[3];

    static EncodeFn fn = nullptr;
    static int np = 0;
    static Scratch* scr = nullptr;
    if (!fn) {
        void* p = nullptr;
        cudaDriverEntryPointQueryResult qr;
        cudaGetDriverEntryPoint("cuTensorMapEncodeTiled", &p, cudaEnableDefault, &qr);
        fn = (EncodeFn)p;
        cudaGetSymbolAddress((void**)&scr, g_scratch);
        cudaFuncSetAttribute(fpn_kernel<NPAIRS>, cudaFuncAttributeMaxDynamicSharedMemorySize, SMEM_BYTES);
        cudaFuncSetAttribute(fpn_kernel<0>, cudaFuncAttributeMaxDynamicSharedMemorySize, SMEM_BYTES);
        cudaLaunchConfig_t cfg = {};
        cfg.gridDim = dim3(2); cfg.blockDim = dim3(NTHREADS); cfg.dynamicSmemBytes = SMEM_BYTES;
        cudaLaunchAttribute at[1];
        at[0].id = cudaLaunchAttributeClusterDimension;
        at[0].val.clusterDim.x = 2; at[0].val.clusterDim.y = 1; at[0].val.clusterDim.z = 1;
        cfg.attrs = at; cfg.numAttrs = 1;
        if (cudaOccupancyMaxActiveClusters(&np, fpn_kernel<0>, &cfg) != cudaSuccess || np < 1) np = 1;
        if (np > NPAIRS) np = NPAIRS;
        while ((NSEG / 4) % np) np--;
    }

    CUtensorMap tm_c, tm_p, tm_wl3, tm_out, tm_p8, tm_w64;
    {
        const cuuint64_t dims[2] = {(cuuint64_t)C, (cuuint64_t)NPIX};
        const cuuint64_t str[1]  = {(cuuint64_t)C * 2};
        const cuuint32_t box_in[2]  = {64, 32};
        const cuuint32_t box_out[2] = {64, 16};
        encode(fn, &tm_c, c_fine, 2, dims, str, box_in);
        encode(fn, &tm_out, d_out, 2, dims, str, box_out);
    }
    {
        const cuuint64_t dims[5] = {(cuuint64_t)C, 2, 4, (cuuint64_t)(2 * np), (cuuint64_t)(NSEG / np)};
        const cuuint64_t str[4]  = {(cuuint64_t)4 * C * 2, (cuuint64_t)C * 2, (cuuint64_t)8 * C * 2, (cuuint64_t)np * 16 * C * 2};
        const cuuint32_t box[5]  = {64, 2, 4, 2, 2};
        encode(fn, &tm_p, p_coarse, 5, dims, str, box);
        const cuuint32_t box8[5] = {64, 2, 4, 2, 4};
        encode(fn, &tm_p8, p_coarse, 5, dims, str, box8);
    }
    {
        const cuuint64_t dims[2] = {(cuuint64_t)C, (cuuint64_t)C};
        const cuuint64_t str[1]  = {(cuuint64_t)C * 2};
        const cuuint32_t box_k[2] = {64, 64};
        encode(fn, &tm_w64, w_out, 2, dims, str, box_k);
    }
    {
        const cuuint64_t dims[3] = {64, (cuuint64_t)C, 6};
        const cuuint64_t str[2]  = {(cuuint64_t)C * 2, 128};
        const cuuint32_t box[3]  = {64, 32, 2};
        encode(fn, &tm_wl3, w_lat, 3, dims, str, box);
    }
    auto kernel = np == NPAIRS ? fpn_kernel<NPAIRS> : fpn_kernel<0>;
    kernel<<<2 * np, NTHREADS, SMEM_BYTES>>>(scr, w_out, c_fine, p_coarse, NSEG / np, 1.0f,
                                             tm_w64, tm_wl3, tm_p8, tm_c, tm_p, tm_out);
}
```

```cpp
#include <cuda_runtime.h>
#include <cuda_bf16.h>
#include <cuda.h>
#include <stdint.h>

namespace {

constexpr int C          = 384;
constexpr int HW         = 384;
constexpr int NPIX       = HW * HW;
constexpr int NSEG       = NPIX / 64;
constexpr int NJOBS      = 36;

constexpr int NFRAG      = 28;
constexpr int NSLOTS     = 10;
constexpr int NPAIRS     = 64;
constexpr int PF_LEAD    = 5;
constexpr int PF_LEAD0   = 17;
constexpr int PF_DECAY   = 11;
constexpr int PF_START   = 3;
constexpr int PF_FIRST   = 9;
constexpr int PF_GAP     = 50;
constexpr int PF_GAP0    = 150;
constexpr int GOV_START  = 18;
constexpr int EF_STEPS   = 10;
constexpr int CLR_AT     = 20;

constexpr int SLOT_BYTES  = 8192;
constexpr int WOUT_SLICE  = 384 * 128;
constexpr int OFF_WOUT    = 0;
constexpr int OFF_RING    = 3 * WOUT_SLICE;
constexpr int OFF_FULL    = OFF_RING + NSLOTS * SLOT_BYTES;
constexpr int OFF_EMPTY   = OFF_FULL + 8 * NSLOTS;
constexpr int OFF_JB2     = OFF_EMPTY + 8 * NSLOTS;
constexpr int OFF_PACE    = OFF_JB2 + 8;
constexpr int SMEM_BYTES  = OFF_PACE + 8;
static_assert(SMEM_BYTES <= 232448, "smem");
static_assert(NSLOTS >= 10, "the first tile (nine ring items) is requested in the prologue");


constexpr int NTHREADS = 512;
constexpr uint64_t POLICY_EVICT_FIRST  = 0x12F0000000000000ull;
constexpr uint64_t POLICY_EVICT_NORMAL = 0x1000000000000000ull;

struct Scratch {
    uint4    wfrag[2 * 6 * NFRAG * 128];
    unsigned epoch;
    unsigned pad0[31];
    unsigned prog;
};
__device__ Scratch g_scratch;

__device__ __forceinline__ uint32_t smem_u32(const void* p) { return (uint32_t)__cvta_generic_to_shared(p); }

__device__ __forceinline__ void mbar_init(uint32_t bar, uint32_t cnt) {
    asm volatile("mbarrier.init.shared::cta.b64 [%0], %1;" ::"r"(bar), "r"(cnt) : "memory");
}
__device__ __forceinline__ void mbar_expect_tx(uint32_t bar, uint32_t bytes) {
    asm volatile("mbarrier.arrive.expect_tx.shared::cta.b64 _, [%0], %1;" ::"r"(bar), "r"(bytes) : "memory");
}
__device__ __forceinline__ void mbar_wait_bounded(uint32_t bar, uint32_t parity) {
    asm volatile(
        "{\n"
        ".reg .pred p;\n"
        ".reg .u32 n;\n"
        "mbarrier.try_wait.parity.shared::cta.b64 p, [%0], %1;\n"
        "@p bra DONE_%=;\n"
        "mov.u32 n, 0;\n"
        "WAIT_%=:\n"
        "mbarrier.try_wait.parity.shared::cta.b64 p, [%0], %1;\n"
        "@p bra DONE_%=;\n"
        "add.u32 n, n, 1;\n"
        "setp.lt.u32 p, n, 4000000;\n"
        "@p bra WAIT_%=;\n"
        "trap;\n"
        "DONE_%=:\n"
        "}\n" ::"r"(bar), "r"(parity) : "memory");
}
__device__ __forceinline__ void mbar_wait(uint32_t bar, uint32_t parity) {
    asm volatile(
        "{\n"
        ".reg .pred p;\n"
        "WAIT_%=:\n"
        "mbarrier.try_wait.parity.shared::cta.b64 p, [%0], %1;\n"
        "@!p bra WAIT_%=;\n"
        "}\n" ::"r"(bar), "r"(parity) : "memory");
}
__device__ __forceinline__ bool mbar_try(uint32_t bar, uint32_t parity) {
    uint32_t r;
    asm volatile("{\n.reg .pred p;\nmbarrier.test_wait.parity.shared::cta.b64 p, [%1], %2;\nselp.u32 %0, 1, 0, p;\n}\n"
                 : "=r"(r) : "r"(bar), "r"(parity) : "memory");
    return r != 0;
}
__device__ __forceinline__ void mbar_arrive_cluster(uint32_t cluster_addr) {
    asm volatile("mbarrier.arrive.shared::cluster.b64 _, [%0];" ::"r"(cluster_addr) : "memory");
}
__device__ __forceinline__ uint32_t mapa(uint32_t addr, uint32_t rank) {
    uint32_t r;
    asm("mapa.shared::cluster.u32 %0, %1, %2;" : "=r"(r) : "r"(addr), "r"(rank));
    return r;
}
__device__ __forceinline__ void named_bar(int wg) {
    asm volatile("bar.sync %0, 128;" ::"r"(wg + 1) : "memory");
}

__device__ __forceinline__ void tma_load_2d(uint32_t dst, const CUtensorMap* tm, int c0, int c1, uint32_t bar) {
    asm volatile("cp.async.bulk.tensor.2d.shared::cluster.global.mbarrier::complete_tx::bytes [%0], [%1, {%2, %3}], [%4];"
                 ::"r"(dst), "l"(tm), "r"(c0), "r"(c1), "r"(bar) : "memory");
}
__device__ __forceinline__ void tma_load_3d(uint32_t dst, const CUtensorMap* tm, int c0, int c1, int c2, uint32_t bar) {
    asm volatile("cp.async.bulk.tensor.3d.shared::cluster.global.mbarrier::complete_tx::bytes [%0], [%1, {%2, %3, %4}], [%5];"
                 ::"r"(dst), "l"(tm), "r"(c0), "r"(c1), "r"(c2), "r"(bar) : "memory");
}
__device__ __forceinline__ void tma_load_5d(uint32_t dst, const CUtensorMap* tm, int c0, int c3, int c4, uint32_t bar) {
    asm volatile("cp.async.bulk.tensor.5d.shared::cluster.global.mbarrier::complete_tx::bytes [%0], [%1, {%2, 0, 0, %3, %4}], [%5];"
                 ::"r"(dst), "l"(tm), "r"(c0), "r"(c3), "r"(c4), "r"(bar) : "memory");
}
__device__ __forceinline__ void tma_load_2d_mc(uint32_t dst, const CUtensorMap* tm, int c0, int c1, uint32_t bar, uint64_t pol) {
    asm volatile("cp.async.bulk.tensor.2d.shared::cluster.global.mbarrier::complete_tx::bytes.multicast::cluster.L2::cache_hint"
                 " [%0], [%1, {%2, %3}], [%4], %5, %6;"
                 ::"r"(dst), "l"(tm), "r"(c0), "r"(c1), "r"(bar), "h"((uint16_t)3), "l"(pol) : "memory");
}
__device__ __forceinline__ void tma_load_5d_mc(uint32_t dst, const CUtensorMap* tm, int c0, int c3, int c4, uint32_t bar, uint64_t pol) {
    asm volatile("cp.async.bulk.tensor.5d.shared::cluster.global.mbarrier::complete_tx::bytes.multicast::cluster.L2::cache_hint"
                 " [%0], [%1, {%2, 0, 0, %3, %4}], [%5], %6, %7;"
                 ::"r"(dst), "l"(tm), "r"(c0), "r"(c3), "r"(c4), "r"(bar), "h"((uint16_t)3), "l"(pol) : "memory");
}
__device__ __forceinline__ void tma_store_2d(const CUtensorMap* tm, int c0, int c1, uint32_t src, uint64_t pol) {
    asm volatile("cp.async.bulk.tensor.2d.global.shared::cta.bulk_group.L2::cache_hint [%0, {%1, %2}], [%3], %4;"
                 ::"l"(tm), "r"(c0), "r"(c1), "r"(src), "l"(pol) : "memory");
}
__device__ __forceinline__ void prefetch_tmap(const CUtensorMap* tm) {
    asm volatile("prefetch.tensormap [%0];" ::"l"(tm) : "memory");
}

__device__ __forceinline__ void wg_fence()  { asm volatile("wgmma.fence.sync.aligned;" ::: "memory"); }
__device__ __forceinline__ void wg_commit() { asm volatile("wgmma.commit_group.sync.aligned;" ::: "memory"); }
template <int N> __device__ __forceinline__ void wg_wait() { asm volatile("wgmma.wait_group.sync.aligned %0;" ::"n"(N) : "memory"); }

#define ACC16(a)                                                                                              \
    "+f"(a[0]), "+f"(a[1]), "+f"(a[2]), "+f"(a[3]), "+f"(a[4]), "+f"(a[5]), "+f"(a[6]), "+f"(a[7]),           \
    "+f"(a[8]), "+f"(a[9]), "+f"(a[10]), "+f"(a[11]), "+f"(a[12]), "+f"(a[13]), "+f"(a[14]), "+f"(a[15])
#define ACC32(a)                                                                                              \
    ACC16(a),                                                                                                 \
    "+f"(a[16]), "+f"(a[17]), "+f"(a[18]), "+f"(a[19]), "+f"(a[20]), "+f"(a[21]), "+f"(a[22]), "+f"(a[23]),   \
    "+f"(a[24]), "+f"(a[25]), "+f"(a[26]), "+f"(a[27]), "+f"(a[28]), "+f"(a[29]), "+f"(a[30]), "+f"(a[31])
#define ACC16_STR "{%0, %1, %2, %3, %4, %5, %6, %7, %8, %9, %10, %11, %12, %13, %14, %15}"
#define ACC32_STR                                                                                             \
    "{%0, %1, %2, %3, %4, %5, %6, %7, %8, %9, %10, %11, %12, %13, %14, %15, "                                 \
    "%16, %17, %18, %19, %20, %21, %22, %23, %24, %25, %26, %27, %28, %29, %30, %31}"

template <int BOFF>
__device__ __forceinline__ void wgmma_rs(float (&d)[32], uint32_t a0, uint32_t a1, uint32_t a2, uint32_t a3, uint32_t db_lo) {
    asm volatile("{\n.reg .b64 db;\n.reg .b32 lo;\n"
                 "add.u32 lo, %36, %37;\nmov.b64 db, {lo, 0x40000040};\n"
                 "wgmma.mma_async.sync.aligned.m64n64k16.f32.bf16.bf16 " ACC32_STR
                 ", {%32, %33, %34, %35}, db, 1, -1, 1, 0;\n}"
                 : ACC32(d) : "r"(a0), "r"(a1), "r"(a2), "r"(a3), "r"(db_lo), "n"(BOFF));
}
template <int ACCUM, int AOFF, int BOFF>
__device__ __forceinline__ void wgmma_ss(float (&d)[32], uint32_t da_lo, uint32_t db_lo) {
    asm volatile("{\n.reg .b64 da, db;\n.reg .b32 lo;\n"
                 "add.u32 lo, %32, %34;\nmov.b64 da, {lo, 0x40000040};\n"
                 "add.u32 lo, %36, %35;\nmov.b64 db, {lo, 0x40000040};\n"
                 "wgmma.mma_async.sync.aligned.m64n64k16.f32.bf16.bf16 " ACC32_STR
                 ", da, db, %33, 1, 1, 1, 0;\n}"
                 : ACC32(d) : "r"(da_lo), "n"(ACCUM), "n"(AOFF), "n"(BOFF), "r"(db_lo));
}
template <int ACCUM, int AOFF, int BOFF>
__device__ __forceinline__ void wgmma_ss32(float (&d)[16], uint32_t da_lo, uint32_t db_lo) {
    asm volatile("{\n.reg .b64 da, db;\n.reg .b32 lo;\n"
                 "add.u32 lo, %16, %18;\nmov.b64 da, {lo, 0x40000040};\n"
                 "add.u32 lo, %20, %19;\nmov.b64 db, {lo, 0x40000040};\n"
                 "wgmma.mma_async.sync.aligned.m64n32k16.f32.bf16.bf16 " ACC16_STR
                 ", da, db, %17, 1, 1, 1, 0;\n}"
                 : ACC16(d) : "r"(da_lo), "n"(ACCUM), "n"(AOFF), "n"(BOFF), "r"(db_lo));
}
__device__ __forceinline__ uint32_t desc_lo(uint32_t addr) { return ((addr & 0x3FFFFu) >> 4) | (1u << 16); }
__device__ __forceinline__ uint32_t pack_bf16(float lo, float hi) {
    uint32_t r;
    asm("cvt.rn.bf16x2.f32 %0, %1, %2;" : "=r"(r) : "f"(hi), "f"(lo));
    return r;
}
__device__ __forceinline__ uint32_t enc_neg(uint32_t pair) {
    const uint32_t v = pair ^ 0x80008000u;
    return v == 0u ? 0x80008000u : v;
}
__device__ __forceinline__ uint32_t pack_neg(float lo, float hi) { return enc_neg(pack_bf16(lo, hi)); }
__device__ __forceinline__ float dup(float x, float one) {
    float r;
    asm volatile("mul.f32 %0, %1, %2;" : "=f"(r) : "f"(x), "f"(one));
    return r;
}
__device__ __forceinline__ void stsm_x4_t(uint32_t addr, uint32_t r0, uint32_t r1, uint32_t r2, uint32_t r3) {
    asm volatile("stmatrix.sync.aligned.m8n8.x4.trans.shared.b16 [%0], {%1, %2, %3, %4};"
                 ::"r"(addr), "r"(r0), "r"(r1), "r"(r2), "r"(r3) : "memory");
}

struct Ctx {
    uint32_t sbase;
    uint32_t db0;
    uint32_t da0;
    uint32_t empty_tgt;
    bool     signal;
};

template <int N> __device__ __forceinline__ constexpr uint32_t slot_of() { return (3 + N) % NSLOTS; }
template <int N> __device__ __forceinline__ uint32_t phase_of(uint32_t pu) { return pu ^ (((3 + N) / NSLOTS) & 1); }
template <int N> __device__ __forceinline__ void release(const Ctx& cx) {
    if (cx.signal) mbar_arrive_cluster(cx.empty_tgt + slot_of<N>() * 8);
}

enum { FINE, COARSE, COARSE_REG };
template <int N, int MODE>
__device__ __forceinline__ void chunk(float (&acc)[32], const uint32_t (&W)[96], const uint32_t (&A)[16], uint32_t zero,
                                      const Ctx& cx, uint32_t pu, bool& ready) {
    constexpr int KC = N % 6;
    constexpr int B  = slot_of<N>() * 512;
    if (!ready) mbar_wait(cx.sbase + OFF_FULL + slot_of<N>() * 8, phase_of<N>(pu));
    ready = mbar_try(cx.sbase + OFF_FULL + slot_of<N + 1>() * 8, phase_of<N + 1>(pu));
    if (MODE == FINE) {
        wg_fence();
        wgmma_rs<B + 0>(acc, W[KC * 16 + 0],  W[KC * 16 + 1],  W[KC * 16 + 2],  W[KC * 16 + 3], cx.db0);
        wgmma_rs<B + 2>(acc, W[KC * 16 + 4],  W[KC * 16 + 5],  W[KC * 16 + 6],  W[KC * 16 + 7], cx.db0);
        wgmma_rs<B + 4>(acc, W[KC * 16 + 8],  W[KC * 16 + 9],  W[KC * 16 + 10], W[KC * 16 + 11], cx.db0);
        wgmma_rs<B + 6>(acc, W[KC * 16 + 12], W[KC * 16 + 13], W[KC * 16 + 14], W[KC * 16 + 15], cx.db0);
    } else {
        if (MODE == COARSE) {
            wg_fence();
            wgmma_ss<(KC > 0), KC * 4 * 128, B>(acc, cx.da0, cx.db0);
        } else {
            uint32_t a[4];
#pragma unroll
            for (int i = 0; i < 4; i++) asm volatile("xor.b32 %0, %1, %2;" : "=r"(a[i]) : "r"(A[((KC + 2) & 3) * 4 + i]), "r"(zero));
            wg_fence();
            wgmma_rs<B>(acc, a[0], a[1], a[2], a[3], cx.db0);
            wg_commit();
        }
        wgmma_ss<1, (KC * 4 + 1) * 128, B + 2>(acc, cx.da0, cx.db0);
        wgmma_ss<1, (KC * 4 + 2) * 128, B + 4>(acc, cx.da0, cx.db0);
        wgmma_ss<1, (KC * 4 + 3) * 128, B + 6>(acc, cx.da0, cx.db0);
    }
    wg_commit();
    if (KC > 0) {
        wg_wait<1>();
        release<N - (KC > 0)>(cx);
    }
}

__device__ __forceinline__ int seg_row(int g) {
    const int y = g / 12;
    return y * (2 * HW) + (g - y * 12) * 32;
}

template <int NP>
__global__ void __cluster_dims__(2, 1, 1) __launch_bounds__(NTHREADS, 1)
fpn_kernel(Scratch* scr,
           const __nv_bfloat16* __restrict__ c_ptr, const __nv_bfloat16* __restrict__ p_ptr, const int nsteps, const float one, const uint32_t zero,
           const __grid_constant__ CUtensorMap tm_w64, const __grid_constant__ CUtensorMap tm_wl3,
           const __grid_constant__ CUtensorMap tm_p8, const __grid_constant__ CUtensorMap tm_c,
           const __grid_constant__ CUtensorMap tm_p, const __grid_constant__ CUtensorMap tm_out)
{
    extern __shared__ __align__(1024) uint8_t smem[];
    const uint32_t sbase = smem_u32(smem);
    const int tid   = threadIdx.x;
    const int warp  = __shfl_sync(0xffffffffu, tid >> 5, 0);
    const int lane  = tid & 31;
    const int rank  = blockIdx.x & 1;
    const int pair  = blockIdx.x >> 1;
    const int npair = NP ? NP : gridDim.x >> 1;
    const int nfine = NP ? NSEG / (NP ? NP : 1) : nsteps;

    if (tid == 480) {
        prefetch_tmap(&tm_w64); prefetch_tmap(&tm_wl3); prefetch_tmap(&tm_p8);
        prefetch_tmap(&tm_c); prefetch_tmap(&tm_p); prefetch_tmap(&tm_out);
    }
    if (tid == 384) {
        for (int s = 0; s < 3; s++) mbar_init(sbase + OFF_FULL + s * 8, 1);
        asm volatile("fence.mbarrier_init.release.cluster;" ::: "memory");
        asm volatile("fence.proxy.async.shared::cta;" ::: "memory");
        const int g0 = pair % 3;
#pragma unroll 1
        for (int s = 0; s < 3; s++) {
            const uint32_t bar = sbase + OFF_FULL + s * 8;
            const uint32_t dst = sbase + OFF_WOUT + g0 * WOUT_SLICE + s * 16384;
            mbar_expect_tx(bar, pair < NJOBS ? 3 * SLOT_BYTES : 2 * SLOT_BYTES);
            tma_load_2d(dst, &tm_w64, rank * 192 + g0 * 64, s * 128, bar);
            if (pair < NJOBS) tma_load_3d(sbase + OFF_RING + s * SLOT_BYTES, &tm_wl3, 0, (pair / 3) * 32, 2 * s, bar);
            tma_load_2d(dst + 8192, &tm_w64, rank * 192 + g0 * 64, s * 128 + 64, bar);
        }
    }
    if (warp == 13) {
        if (lane == 0) {
            for (int s = 0; s < NSLOTS; s++) {
                if (s >= 3) mbar_init(sbase + OFF_FULL + s * 8, 1);
                mbar_init(sbase + OFF_EMPTY + s * 8, 6);
            }
            mbar_init(sbase + OFF_JB2, 1);
            asm volatile("st.volatile.shared.u32 [%0], %1;" ::"r"(sbase + OFF_PACE), "r"(6) : "memory");
            asm volatile("fence.mbarrier_init.release.cluster;" ::: "memory");
            asm volatile("fence.proxy.async.shared::cta;" ::: "memory");
        }
        __syncwarp();
        asm volatile("bar.arrive 5, 448;" ::: "memory");
    }
    __syncwarp();
    asm volatile("barrier.cluster.arrive.relaxed.aligned;" ::: "memory");

    if (warp >= 12) {
        asm volatile("setmaxnreg.dec.sync.aligned.u32 32;");
        if (warp == 12) {
            asm volatile("bar.sync 5, 448;" ::: "memory");
            if (lane == 0) {
                const int g1 = (pair + 1) % 3, g2 = (pair + 2) % 3;
#pragma unroll 1
                for (int kc = 0; kc < 6; kc++) {
                    const uint32_t bar = sbase + OFF_FULL + (3 + kc) * 8;
                    mbar_expect_tx(bar, 3 * SLOT_BYTES);
                    tma_load_5d(sbase + OFF_RING + (3 + kc) * SLOT_BYTES, &tm_p8, kc * 64, pair * 2, 0, bar);
                    tma_load_2d(sbase + OFF_WOUT + g1 * WOUT_SLICE + kc * 8192, &tm_w64, rank * 192 + g1 * 64, kc * 64, bar);
                    tma_load_2d(sbase + OFF_WOUT + g2 * WOUT_SLICE + kc * 8192, &tm_w64, rank * 192 + g2 * 64, kc * 64, bar);
                }
            }
            __syncwarp();
        }
        asm volatile("barrier.cluster.wait.aligned;" ::: "memory");
        if (warp == 12) {
            if (lane == 0) {
                const uint32_t dst0 = sbase + OFF_RING + rank * 4096;
                uint32_t so = 9 * 8, ph = 1, step = 6;
                auto acquire = [&](uint32_t& bar, uint32_t& dst) {
                    bar = sbase + OFF_FULL + so;
                    dst = dst0 + so * (SLOT_BYTES / 8);
                    mbar_wait_bounded(sbase + OFF_EMPTY + so, ph);
                    mbar_expect_tx(bar, SLOT_BYTES);
                };
                auto next_slot = [&]() {
                    so += 8;
                    if (so == NSLOTS * 8) { so = 0; ph ^= 1; }
                };
                auto advance = [&]() {
                    next_slot();
                    step++;
                    asm volatile("st.volatile.shared.u32 [%0], %1;" ::"r"(sbase + OFF_PACE), "r"(step) : "memory");
                };
                unsigned mytiles = 0, seen = 0;
                auto look = [&]() {
                    asm volatile("ld.relaxed.gpu.global.u32 %0, [%1];" : "=r"(seen) : "l"(&scr->prog) : "memory");
                };
                auto count = [&]() {
                    asm volatile("red.relaxed.gpu.global.add.u32 [%0], 1;" ::"l"(&scr->prog) : "memory");
                };
                auto govern = [&]() {
                    if (rank == 0) {
                        unsigned spins = 0;
                        while (mytiles >= GOV_START && mytiles * npair > seen && ++spins < 100000u) look();
                        mytiles++;
                    }
                };
#pragma unroll 1
                for (int j = 0; j < nfine; j++) {
                    const uint64_t pol = j >= nfine - EF_STEPS ? POLICY_EVICT_FIRST : POLICY_EVICT_NORMAL;
                    if ((j & 3) == 0 && j > 0) {
                        govern();
#pragma unroll
                        for (int kc = 0; kc < 6; kc++) {
                            uint32_t bar, dst;
                            acquire(bar, dst);
                            tma_load_5d_mc(dst, &tm_p, kc * 64, pair * 2, j + 2 * rank, bar, pol);
                            advance();
                            if (kc == 0 && rank == 0) count();
                            if (kc == 3 && rank == 0) look();
                        }
                    }
                    const int row = seg_row(j * npair + pair) + rank * HW;
                    govern();
#pragma unroll
                    for (int kc = 0; kc < 6; kc++) {
                        uint32_t bar, dst;
                        acquire(bar, dst);
                        tma_load_2d_mc(dst, &tm_c, kc * 64, row, bar, pol);
                        advance();
                        if (kc == 0 && rank == 0 && j + 1 < nfine) count();
                        if (kc == 3 && rank == 0) look();
                    }
                }
                if (rank == 0) {
                    if (atomicAdd(&scr->prog, 1u) + 1 == mytiles * npair) {
                        asm volatile("st.relaxed.gpu.global.u32 [%0], 0;" ::"l"(&scr->prog) : "memory");
                        asm volatile("red.relaxed.gpu.global.add.u32 [%0], 1;" ::"l"(&scr->epoch) : "memory");
                    }
                }
                for (int s = 0; s < NSLOTS; s++) {
                    mbar_wait_bounded(sbase + OFF_EMPTY + so, ph);
                    next_slot();
                }
            }
        } else if (warp == 13) {
#pragma unroll 1
            for (int i = PF_START; i < nfine + nfine / 4; i++) {
                const int k5 = i / 5, t = i - k5 * 5;
                const char *b0, *b1;
                if (t == 0) {
                    b0 = (const char*)p_ptr + (size_t)((4 * k5 + 2 * rank) * npair + pair) * (16 * C * 2);
                    b1 = b0 + (size_t)npair * (16 * C * 2);
                } else {
                    b0 = (const char*)c_ptr + (size_t)(seg_row((4 * k5 + t - 1) * npair + pair) + rank * HW) * (C * 2);
                    b1 = b0 + 16 * C * 2;
                }
                const int need = max(6 * i - max(PF_LEAD0 - max(i - PF_DECAY, 0), PF_LEAD), PF_FIRST);
                unsigned spins = 0;
                while (true) {
                    uint32_t v;
                    asm volatile("ld.volatile.shared.u32 %0, [%1];" : "=r"(v) : "r"(sbase + OFF_PACE) : "memory");
                    if ((int)v >= need || ++spins > 4000000u) break;
                    __nanosleep(20);
                }
#pragma unroll
                for (int k = 0; k < 6; k++) {
                    asm volatile("prefetch.global.L2 [%0];" ::"l"((k < 3 ? b0 : b1) + lane * 128 + (k % 3) * 4096) : "memory");
                    __nanosleep(i < PF_START + 2 ? PF_GAP0 : PF_GAP);
                }
            }
        } else if (warp == 15) {
            uint32_t par, v;
            asm volatile("ld.relaxed.gpu.global.u32 %0, [%1];" : "=r"(par) : "l"(&scr->epoch) : "memory");
            uint4* clr = scr->wfrag + (~par & 1) * (6 * NFRAG * 128);
            unsigned spins = 0;
            do {
                __nanosleep(500);
                asm volatile("ld.volatile.shared.u32 %0, [%1];" : "=r"(v) : "r"(sbase + OFF_PACE) : "memory");
            } while (v < CLR_AT && ++spins < 100000u);
            for (int i = blockIdx.x * 32 + lane; i < 6 * NFRAG * 128; i += npair * 64) clr[i] = make_uint4(0u, 0u, 0u, 0u);
        }
    } else {
        uint32_t par;
        asm volatile("ld.relaxed.gpu.global.u32 %0, [%1];" : "=r"(par) : "l"(&scr->epoch) : "memory");
        asm volatile("setmaxnreg.inc.sync.aligned.u32 160;");
        asm volatile("bar.sync 5, 448;" ::: "memory");
        const int wg   = warp >> 2;
        const int wtid = tid & 127;
        Ctx cx;
        cx.sbase     = sbase;
        cx.empty_tgt = mapa(sbase + OFF_EMPTY, warp & 1);
        cx.signal    = (lane == 0) && ((warp & 3) < 2);
        cx.db0       = desc_lo(sbase + OFF_RING);
        cx.da0       = desc_lo(sbase + OFF_WOUT + wg * WOUT_SLICE);
        const int cb = rank * 3 + wg;

        float    acc[32];
        uint32_t qp[16];
        uint32_t W[96];

        {
            uint32_t jph = 0;
            for (int job = pair; job < NJOBS; job += npair) {
                if (job % 3 == wg) {
                    if (job != pair) {
                        named_bar(wg);
                        if (wtid == 0) {
                            mbar_expect_tx(sbase + OFF_JB2, 6 * 4096);
                            for (int s = 0; s < 3; s++)
                                tma_load_3d(sbase + OFF_RING + s * SLOT_BYTES, &tm_wl3, 0, (job / 3) * 32, 2 * s, sbase + OFF_JB2);
                        }
                        for (int kc = 0; kc < 6; kc++) mbar_wait(sbase + OFF_FULL + (3 + kc) * 8, 0);
                        mbar_wait(sbase + OFF_JB2, jph);
                    }
                    float ja[16];
#define JOBK(k) wgmma_ss32<((k) > 0), (k) * 128, ((k) >> 2) * 256 + ((k) & 3) * 2>(ja, cx.da0, cx.db0);
                    mbar_wait(sbase + OFF_FULL, 0);
                    wg_fence();
                    JOBK(0)  JOBK(1)  JOBK(2)  JOBK(3)  JOBK(4)  JOBK(5)  JOBK(6)  JOBK(7)
                    wg_commit();
                    mbar_wait(sbase + OFF_FULL + 8, 0);
                    wg_fence();
                    JOBK(8)  JOBK(9)  JOBK(10) JOBK(11) JOBK(12) JOBK(13) JOBK(14) JOBK(15)
                    wg_commit();
                    mbar_wait(sbase + OFF_FULL + 16, 0);
                    wg_fence();
                    JOBK(16) JOBK(17) JOBK(18) JOBK(19) JOBK(20) JOBK(21) JOBK(22) JOBK(23)
#undef JOBK
                    wg_commit();
                    wg_wait<0>();
                    const int fidx = (cb * NFRAG + (job / 3) * 2) * 128 + wtid;
                    uint4* dst = scr->wfrag + (par & 1) * (6 * NFRAG * 128) + fidx;
#pragma unroll
                    for (int i = 0; i < 2; i++) {
                        asm volatile("st.relaxed.gpu.global.v4.u32 [%0], {%1, %2, %3, %4};" ::"l"(dst + i * 128),
                                     "r"(pack_neg(ja[8 * i + 0], ja[8 * i + 1])), "r"(pack_neg(ja[8 * i + 2], ja[8 * i + 3])),
                                     "r"(pack_neg(ja[8 * i + 4], ja[8 * i + 5])), "r"(pack_neg(ja[8 * i + 6], ja[8 * i + 7])) : "memory");
                    }
                }
                if (job + npair < NJOBS) asm volatile("bar.sync 4, 384;" ::: "memory");
                if (job != pair) jph ^= 1;
            }
        }

        par &= 1;
        if (pair < NJOBS) asm volatile("bar.sync 6, 384;" ::: "memory");
        asm volatile("barrier.cluster.wait.aligned;" ::: "memory");

        mbar_wait(sbase + OFF_FULL, 0);
        mbar_wait(sbase + OFF_FULL + 8, 0);
        mbar_wait(sbase + OFF_FULL + 16, 0);
        if (cx.signal) {
            mbar_arrive_cluster(cx.empty_tgt);
            mbar_arrive_cluster(cx.empty_tgt + 8);
            mbar_arrive_cluster(cx.empty_tgt + 16);
        }
        auto pack_q = [&]() {
            uint32_t all = 0;
#pragma unroll
            for (int i = 0; i < 16; i++) {
                qp[i] = pack_bf16(acc[2 * i], acc[2 * i + 1]);
                if (i >= 4) all |= qp[i];
            }
            qp[3] |= all & zero;
        };
        bool ready = false;
        uint32_t pu = 0;
#define CHUNK(N, MODE) chunk<N, MODE>(acc, W, qp, zero, cx, pu, ready)

        const uint4* wsrc = scr->wfrag + (par * 6 + cb) * (NFRAG * 128) + wtid;
        auto load_w = [&](int kc) {
#pragma unroll
            for (int s = 4 * kc; s < 4 * kc + 4; s++) {
                asm volatile("ld.relaxed.gpu.global.v4.u32 {%0, %1, %2, %3}, [%4];"
                             : "=r"(W[4 * s]), "=r"(W[4 * s + 1]), "=r"(W[4 * s + 2]), "=r"(W[4 * s + 3])
                             : "l"(wsrc + s * 128) : "memory");
            }
        };
        auto check_w = [&](int kc) {
            uint32_t* w = kc < 6 ? W + 16 * kc : qp;
            asm volatile(
                "{\n.reg .pred p;\n.reg .u32 m, n;\n"
                "mov.u32 n, 0;\n"
                "CHK_%=:\n"
                "mov.u32 m, %%clock;\n or.b32 m, m, 1;\n min.u32 m, m, %0;\n"
                "min.u32 m, m, %1;\n min.u32 m, m, %2;\n min.u32 m, m, %3;\n min.u32 m, m, %4;\n min.u32 m, m, %5;\n"
                "min.u32 m, m, %6;\n min.u32 m, m, %7;\n min.u32 m, m, %8;\n min.u32 m, m, %9;\n min.u32 m, m, %10;\n"
                "min.u32 m, m, %11;\n min.u32 m, m, %12;\n min.u32 m, m, %13;\n min.u32 m, m, %14;\n min.u32 m, m, %15;\n"
                "setp.ne.u32 p, m, 0;\n"
                "vote.sync.all.pred p, p, 0xffffffff;\n"
                "@p bra.uni OK_%=;\n"
                "add.u32 n, n, 1;\n"
                "setp.gt.u32 p, n, 5000000;\n"
                "@p bra.uni OK_%=;\n"
                "ld.relaxed.gpu.global.v4.u32 {%0, %1, %2, %3}, [%16];\n"
                "ld.relaxed.gpu.global.v4.u32 {%4, %5, %6, %7}, [%16 + 2048];\n"
                "ld.relaxed.gpu.global.v4.u32 {%8, %9, %10, %11}, [%16 + 4096];\n"
                "ld.relaxed.gpu.global.v4.u32 {%12, %13, %14, %15}, [%16 + 6144];\n"
                "bra.uni CHK_%=;\n"
                "OK_%=:\n}"
                : "+r"(w[0]), "+r"(w[1]), "+r"(w[2]), "+r"(w[3]), "+r"(w[4]), "+r"(w[5]), "+r"(w[6]), "+r"(w[7]),
                  "+r"(w[8]), "+r"(w[9]), "+r"(w[10]), "+r"(w[11]), "+r"(w[12]), "+r"(w[13]), "+r"(w[14]), "+r"(w[15])
                : "l"(wsrc + kc * 512) : "memory");
        };
        const uint32_t stage = sbase + OFF_WOUT + wg * WOUT_SLICE + 2 * 8192;
        const uint32_t st_addr = stage + (((lane >> 4) * 8 + (lane & 7)) << 7)
                               + (((((warp & 3) << 1) | ((lane >> 3) & 1)) ^ (lane & 7)) << 4);
        auto publish = [&](int s) {
            if (pair == (NJOBS + s) % npair) {
                uint32_t a[4];
                asm volatile("ldmatrix.sync.aligned.m8n8.x4.trans.shared.b16 {%0, %1, %2, %3}, [%4];"
                             : "=r"(a[0]), "=r"(a[1]), "=r"(a[2]), "=r"(a[3]) : "r"(st_addr + s * 8192) : "memory");
                asm volatile("st.relaxed.gpu.global.v4.u32 [%0], {%1, %2, %3, %4};" ::"l"(wsrc + (24 + s) * 128),
                             "r"(enc_neg(a[0])), "r"(enc_neg(a[1])), "r"(enc_neg(a[2])), "r"(enc_neg(a[3])) : "memory");
            }
        };
        CHUNK(0, COARSE);
        CHUNK(1, COARSE);
        CHUNK(2, COARSE);
        publish(0);
        load_w(0);
        CHUNK(3, COARSE);
        publish(1);
        load_w(1);
        CHUNK(4, COARSE);
        publish(2);
        load_w(2);
        CHUNK(5, COARSE);
        publish(3);
        wg_wait<0>();
        release<5>(cx);
        pack_q();

        auto flush_part = [&](int row, int part) {
            if (part == 0) {
                asm volatile("fence.proxy.async.shared::cta;" ::: "memory");
                named_bar(wg);
            }
            if (wtid == 0) {
                tma_store_2d(&tm_out, cb * 64, row + (part >> 1) * HW + (part & 1) * 16, stage + part * 8192, POLICY_EVICT_FIRST);
                if (part == 3) asm volatile("cp.async.bulk.commit_group;" ::: "memory");
            }
        };
        auto init_acc = [&](int t) {
#pragma unroll
            for (int b = 0; b < 2; b++) {
#pragma unroll
                for (int h = 0; h < 2; h++) {
                    const uint32_t q = qp[t * 4 + b * 2 + h];
                    const float lo = __uint_as_float(q << 16), hi = __uint_as_float(q & 0xffff0000u);
#pragma unroll
                    for (int dy = 0; dy < 2; dy++) {
                        acc[16 * dy + 8 * b + 2 * h]         = dy ? dup(lo, one) : lo;
                        acc[16 * dy + 8 * b + 2 * h + 1]     = dup(lo, one);
                        acc[16 * dy + 8 * b + 4 + 2 * h]     = dy ? dup(hi, one) : hi;
                        acc[16 * dy + 8 * b + 4 + 2 * h + 1] = dup(hi, one);
                    }
                }
            }
        };
        auto stage_tile = [&](int slot) {
            if (wtid == 0) asm volatile("cp.async.bulk.wait_group.read 0;" ::: "memory");
            named_bar(wg);
            wg_wait<0>();
            if (cx.signal) mbar_arrive_cluster(cx.empty_tgt + slot * 8);
#pragma unroll
            for (int i = 0; i < 8; i += 2) {
                stsm_x4_t(st_addr + i * 4096,
                          pack_bf16(acc[4 * i + 0], acc[4 * i + 1]), pack_bf16(acc[4 * i + 2], acc[4 * i + 3]),
                          pack_bf16(acc[4 * i + 4], acc[4 * i + 5]), pack_bf16(acc[4 * i + 6], acc[4 * i + 7]));
            }
        };

        auto load_wo = [&]() {
#pragma unroll
            for (int s = 0; s < 4; s++) {
                asm volatile("ld.global.ca.v4.u32 {%0, %1, %2, %3}, [%4];"
                             : "=r"(qp[4 * s]), "=r"(qp[4 * s + 1]), "=r"(qp[4 * s + 2]), "=r"(qp[4 * s + 3])
                             : "l"(wsrc + (24 + s) * 128) : "memory");
            }
        };

        init_acc(0);
        check_w(0);
        load_w(3);
        load_w(4);
        CHUNK(6, FINE);
        check_w(1);
        CHUNK(7, FINE);
        check_w(2);
        CHUNK(8, FINE);
        check_w(3);
        load_w(5);
        CHUNK(9, FINE);
        check_w(4);
        CHUNK(10, FINE);
        check_w(5);
        CHUNK(11, FINE);

        int seg = pair;
        int prow = seg_row(seg);
        while (true) {
            stage_tile(slot_of<11>());
            init_acc(1);
            CHUNK(12, FINE);
            flush_part(prow, 0);
            CHUNK(13, FINE);
            CHUNK(14, FINE);
            CHUNK(15, FINE);
            flush_part(prow, 1);
            flush_part(prow, 2);
            CHUNK(16, FINE);
            flush_part(prow, 3);
            CHUNK(17, FINE);
            seg += npair;
            prow = seg_row(seg);
            stage_tile(slot_of<17>());
            init_acc(2);
            CHUNK(18, FINE);
            flush_part(prow, 0);
            CHUNK(19, FINE);
            CHUNK(20, FINE);
            CHUNK(21, FINE);
            flush_part(prow, 1);
            flush_part(prow, 2);
            CHUNK(22, FINE);
            flush_part(prow, 3);
            CHUNK(23, FINE);
            seg += npair;
            prow = seg_row(seg);
            stage_tile(slot_of<23>());
            init_acc(3);
            CHUNK(24, FINE);
            flush_part(prow, 0);
            CHUNK(25, FINE);
            load_wo();
            CHUNK(26, FINE);
            CHUNK(27, FINE);
            flush_part(prow, 1);
            flush_part(prow, 2);
            CHUNK(28, FINE);
            flush_part(prow, 3);
            CHUNK(29, FINE);
            seg += npair;
            prow = seg_row(seg);
            if (seg + npair >= NSEG) break;
            stage_tile(slot_of<29>());
            CHUNK(30, COARSE);
            flush_part(prow, 0);
            CHUNK(31, COARSE);
            check_w(6);
            CHUNK(32, COARSE_REG);
            flush_part(prow, 1);
            CHUNK(33, COARSE_REG);
            CHUNK(34, COARSE_REG);
            flush_part(prow, 2);
            CHUNK(35, COARSE_REG);
            flush_part(prow, 3);
            wg_wait<0>();
            release<35>(cx);
            pack_q();
            init_acc(0);
            CHUNK(36, FINE);
            CHUNK(37, FINE);
            CHUNK(38, FINE);
            CHUNK(39, FINE);
            CHUNK(40, FINE);
            CHUNK(41, FINE);
            seg += npair;
            prow = seg_row(seg);
            pu ^= 1;
        }
#undef CHUNK
        stage_tile(slot_of<29>());
#pragma unroll
        for (int part = 0; part < 4; part++) flush_part(prow, part);
        if (wtid == 0) asm volatile("cp.async.bulk.wait_group.read 0;" ::: "memory");
    }
}

typedef CUresult (*EncodeFn)(CUtensorMap*, CUtensorMapDataType, cuuint32_t, void*, const cuuint64_t*, const cuuint64_t*,
                             const cuuint32_t*, const cuuint32_t*, CUtensorMapInterleave, CUtensorMapSwizzle,
                             CUtensorMapL2promotion, CUtensorMapFloatOOBfill);

void encode(EncodeFn fn, CUtensorMap* tm, const void* ptr, int rank, const cuuint64_t* dims, const cuuint64_t* strides,
            const cuuint32_t* box) {
    const cuuint32_t es[5] = {1, 1, 1, 1, 1};
    fn(tm, CU_TENSOR_MAP_DATA_TYPE_BFLOAT16, (cuuint32_t)rank, const_cast<void*>(ptr), dims, strides, box, es,
       CU_TENSOR_MAP_INTERLEAVE_NONE, CU_TENSOR_MAP_SWIZZLE_128B, CU_TENSOR_MAP_L2_PROMOTION_NONE,
       CU_TENSOR_MAP_FLOAT_OOB_FILL_NONE);
}

}

extern "C" void kernel_launch(void* const* d_in, const int* in_sizes, int n_in, void* d_out, int out_size) {
    (void)in_sizes; (void)n_in; (void)out_size;
    const __nv_bfloat16* c_fine   = (const __nv_bfloat16*)d_in[0];
    const __nv_bfloat16* p_coarse = (const __nv_bfloat16*)d_in[1];
    const __nv_bfloat16* w_lat    = (const __nv_bfloat16*)d_in[2];
    const __nv_bfloat16* w_out    = (const __nv_bfloat16*)d_in[3];

    static EncodeFn fn = nullptr;
    static int np = 0;
    static Scratch* scr = nullptr;
    if (!fn) {
        void* p = nullptr;
        cudaDriverEntryPointQueryResult qr;
        cudaGetDriverEntryPoint("cuTensorMapEncodeTiled", &p, cudaEnableDefault, &qr);
        fn = (EncodeFn)p;
        cudaGetSymbolAddress((void**)&scr, g_scratch);
        cudaFuncSetAttribute(fpn_kernel<NPAIRS>, cudaFuncAttributeMaxDynamicSharedMemorySize, SMEM_BYTES);
        cudaFuncSetAttribute(fpn_kernel<0>, cudaFuncAttributeMaxDynamicSharedMemorySize, SMEM_BYTES);
        cudaLaunchConfig_t cfg = {};
        cfg.gridDim = dim3(2); cfg.blockDim = dim3(NTHREADS); cfg.dynamicSmemBytes = SMEM_BYTES;
        cudaLaunchAttribute at[1];
        at[0].id = cudaLaunchAttributeClusterDimension;
        at[0].val.clusterDim.x = 2; at[0].val.clusterDim.y = 1; at[0].val.clusterDim.z = 1;
        cfg.attrs = at; cfg.numAttrs = 1;
        if (cudaOccupancyMaxActiveClusters(&np, fpn_kernel<0>, &cfg) != cudaSuccess || np < 1) np = 1;
        if (np > NPAIRS) np = NPAIRS;
        while ((NSEG / 4) % np) np--;
    }

    CUtensorMap tm_c, tm_p, tm_wl3, tm_out, tm_p8, tm_w64;
    {
        const cuuint64_t dims[2] = {(cuuint64_t)C, (cuuint64_t)NPIX};
        const cuuint64_t str[1]  = {(cuuint64_t)C * 2};
        const cuuint32_t box_in[2]  = {64, 32};
        const cuuint32_t box_out[2] = {64, 16};
        encode(fn, &tm_c, c_fine, 2, dims, str, box_in);
        encode(fn, &tm_out, d_out, 2, dims, str, box_out);
    }
    {
        const cuuint64_t dims[5] = {(cuuint64_t)C, 2, 4, (cuuint64_t)(2 * np), (cuuint64_t)(NSEG / np)};
        const cuuint64_t str[4]  = {(cuuint64_t)4 * C * 2, (cuuint64_t)C * 2, (cuuint64_t)8 * C * 2, (cuuint64_t)np * 16 * C * 2};
        const cuuint32_t box[5]  = {64, 2, 4, 2, 2};
        encode(fn, &tm_p, p_coarse, 5, dims, str, box);
        const cuuint32_t box8[5] = {64, 2, 4, 2, 4};
        encode(fn, &tm_p8, p_coarse, 5, dims, str, box8);
    }
    {
        const cuuint64_t dims[2] = {(cuuint64_t)C, (cuuint64_t)C};
        const cuuint64_t str[1]  = {(cuuint64_t)C * 2};
        const cuuint32_t box_k[2] = {64, 64};
        encode(fn, &tm_w64, w_out, 2, dims, str, box_k);
    }
    {
        const cuuint64_t dims[3] = {64, (cuuint64_t)C, 6};
        const cuuint64_t str[2]  = {(cuuint64_t)C * 2, 128};
        const cuuint32_t box[3]  = {64, 32, 2};
        encode(fn, &tm_wl3, w_lat, 3, dims, str, box);
    }
    auto kernel = np == NPAIRS ? fpn_kernel<NPAIRS> : fpn_kernel<0>;
    kernel<<<2 * np, NTHREADS, SMEM_BYTES>>>(scr, c_fine, p_coarse, NSEG / np, 1.0f, 0u,
                                             tm_w64, tm_wl3, tm_p8, tm_c, tm_p, tm_out);
}
```

```cpp
#include <cuda_runtime.h>
#include <cuda_bf16.h>
#include <cuda.h>
#include <stdint.h>

namespace {

constexpr int C          = 384;
constexpr int HW         = 384;
constexpr int NPIX       = HW * HW;
constexpr int NSEG       = NPIX / 64;
constexpr int NJOBS      = 36;

constexpr int NFRAG      = 28;
constexpr int NSLOTS     = 10;
constexpr int NPAIRS     = 64;
constexpr int PF_LEAD    = 5;
constexpr int PF_LEAD0   = 18;
constexpr int PF_DECAY   = 11;
constexpr int PF_START   = 3;
constexpr int PF_FIRST   = 9;
constexpr int PF_GAP     = 50;
constexpr int PF_GAP0    = 150;
constexpr int GOV_START  = 10;
constexpr int GOV_TIGHT  = 24;
constexpr int EF_STEPS   = 10;
constexpr int CLR_AT     = 20;

constexpr int SLOT_BYTES  = 8192;
constexpr int WOUT_SLICE  = 384 * 128;
constexpr int OFF_WOUT    = 0;
constexpr int OFF_RING    = 3 * WOUT_SLICE;
constexpr int OFF_FULL    = OFF_RING + NSLOTS * SLOT_BYTES;
constexpr int OFF_EMPTY   = OFF_FULL + 8 * NSLOTS;
constexpr int OFF_JB2     = OFF_EMPTY + 8 * NSLOTS;
constexpr int OFF_PACE    = OFF_JB2 + 8;
constexpr int SMEM_BYTES  = OFF_PACE + 8;
static_assert(SMEM_BYTES <= 232448, "smem");
static_assert(NSLOTS >= 10, "the first tile (nine ring items) is requested in the prologue");


constexpr int NTHREADS = 512;
constexpr uint64_t POLICY_EVICT_FIRST  = 0x12F0000000000000ull;
constexpr uint64_t POLICY_EVICT_NORMAL = 0x1000000000000000ull;

struct Scratch {
    uint4    wfrag[2 * 6 * NFRAG * 128];
    unsigned epoch;
    unsigned pad0[31];
    unsigned prog;
};
__device__ Scratch g_scratch;

__device__ __forceinline__ uint32_t smem_u32(const void* p) { return (uint32_t)__cvta_generic_to_shared(p); }

__device__ __forceinline__ void mbar_init(uint32_t bar, uint32_t cnt) {
    asm volatile("mbarrier.init.shared::cta.b64 [%0], %1;" ::"r"(bar), "r"(cnt) : "memory");
}
__device__ __forceinline__ void mbar_expect_tx(uint32_t bar, uint32_t bytes) {
    asm volatile("mbarrier.arrive.expect_tx.shared::cta.b64 _, [%0], %1;" ::"r"(bar), "r"(bytes) : "memory");
}
__device__ __forceinline__ void mbar_wait_bounded(uint32_t bar, uint32_t parity) {
    asm volatile(
        "{\n"
        ".reg .pred p;\n"
        ".reg .u32 n;\n"
        "mbarrier.try_wait.parity.shared::cta.b64 p, [%0], %1;\n"
        "@p bra DONE_%=;\n"
        "mov.u32 n, 0;\n"
        "WAIT_%=:\n"
        "mbarrier.try_wait.parity.shared::cta.b64 p, [%0], %1;\n"
        "@p bra DONE_%=;\n"
        "add.u32 n, n, 1;\n"
        "setp.lt.u32 p, n, 4000000;\n"
        "@p bra WAIT_%=;\n"
        "trap;\n"
        "DONE_%=:\n"
        "}\n" ::"r"(bar), "r"(parity) : "memory");
}
__device__ __forceinline__ void mbar_wait(uint32_t bar, uint32_t parity) {
    asm volatile(
        "{\n"
        ".reg .pred p;\n"
        "WAIT_%=:\n"
        "mbarrier.try_wait.parity.shared::cta.b64 p, [%0], %1;\n"
        "@!p bra WAIT_%=;\n"
        "}\n" ::"r"(bar), "r"(parity) : "memory");
}
__device__ __forceinline__ bool mbar_try(uint32_t bar, uint32_t parity) {
    uint32_t r;
    asm volatile("{\n.reg .pred p;\nmbarrier.test_wait.parity.shared::cta.b64 p, [%1], %2;\nselp.u32 %0, 1, 0, p;\n}\n"
                 : "=r"(r) : "r"(bar), "r"(parity) : "memory");
    return r != 0;
}
__device__ __forceinline__ void mbar_arrive_cluster(uint32_t cluster_addr) {
    asm volatile("mbarrier.arrive.shared::cluster.b64 _, [%0];" ::"r"(cluster_addr) : "memory");
}
__device__ __forceinline__ uint32_t mapa(uint32_t addr, uint32_t rank) {
    uint32_t r;
    asm("mapa.shared::cluster.u32 %0, %1, %2;" : "=r"(r) : "r"(addr), "r"(rank));
    return r;
}
__device__ __forceinline__ void named_bar(int wg) {
    asm volatile("bar.sync %0, 128;" ::"r"(wg + 1) : "memory");
}

__device__ __forceinline__ void tma_load_2d(uint32_t dst, const CUtensorMap* tm, int c0, int c1, uint32_t bar) {
    asm volatile("cp.async.bulk.tensor.2d.shared::cluster.global.mbarrier::complete_tx::bytes [%0], [%1, {%2, %3}], [%4];"
                 ::"r"(dst), "l"(tm), "r"(c0), "r"(c1), "r"(bar) : "memory");
}
__device__ __forceinline__ void tma_load_3d(uint32_t dst, const CUtensorMap* tm, int c0, int c1, int c2, uint32_t bar) {
    asm volatile("cp.async.bulk.tensor.3d.shared::cluster.global.mbarrier::complete_tx::bytes [%0], [%1, {%2, %3, %4}], [%5];"
                 ::"r"(dst), "l"(tm), "r"(c0), "r"(c1), "r"(c2), "r"(bar) : "memory");
}
__device__ __forceinline__ void tma_load_5d(uint32_t dst, const CUtensorMap* tm, int c0, int c3, int c4, uint32_t bar) {
    asm volatile("cp.async.bulk.tensor.5d.shared::cluster.global.mbarrier::complete_tx::bytes [%0], [%1, {%2, 0, 0, %3, %4}], [%5];"
                 ::"r"(dst), "l"(tm), "r"(c0), "r"(c3), "r"(c4), "r"(bar) : "memory");
}
__device__ __forceinline__ void tma_load_2d_mc(uint32_t dst, const CUtensorMap* tm, int c0, int c1, uint32_t bar, uint64_t pol) {
    asm volatile("cp.async.bulk.tensor.2d.shared::cluster.global.mbarrier::complete_tx::bytes.multicast::cluster.L2::cache_hint"
                 " [%0], [%1, {%2, %3}], [%4], %5, %6;"
                 ::"r"(dst), "l"(tm), "r"(c0), "r"(c1), "r"(bar), "h"((uint16_t)3), "l"(pol) : "memory");
}
__device__ __forceinline__ void tma_load_5d_mc(uint32_t dst, const CUtensorMap* tm, int c0, int c3, int c4, uint32_t bar, uint64_t pol) {
    asm volatile("cp.async.bulk.tensor.5d.shared::cluster.global.mbarrier::complete_tx::bytes.multicast::cluster.L2::cache_hint"
                 " [%0], [%1, {%2, 0, 0, %3, %4}], [%5], %6, %7;"
                 ::"r"(dst), "l"(tm), "r"(c0), "r"(c3), "r"(c4), "r"(bar), "h"((uint16_t)3), "l"(pol) : "memory");
}
__device__ __forceinline__ void tma_store_2d(const CUtensorMap* tm, int c0, int c1, uint32_t src, uint64_t pol) {
    asm volatile("cp.async.bulk.tensor.2d.global.shared::cta.bulk_group.L2::cache_hint [%0, {%1, %2}], [%3], %4;"
                 ::"l"(tm), "r"(c0), "r"(c1), "r"(src), "l"(pol) : "memory");
}
__device__ __forceinline__ void prefetch_tmap(const CUtensorMap* tm) {
    asm volatile("prefetch.tensormap [%0];" ::"l"(tm) : "memory");
}

__device__ __forceinline__ void wg_fence()  { asm volatile("wgmma.fence.sync.aligned;" ::: "memory"); }
__device__ __forceinline__ void wg_commit() { asm volatile("wgmma.commit_group.sync.aligned;" ::: "memory"); }
template <int N> __device__ __forceinline__ void wg_wait() { asm volatile("wgmma.wait_group.sync.aligned %0;" ::"n"(N) : "memory"); }

#define ACC16(a)                                                                                              \
    "+f"(a[0]), "+f"(a[1]), "+f"(a[2]), "+f"(a[3]), "+f"(a[4]), "+f"(a[5]), "+f"(a[6]), "+f"(a[7]),           \
    "+f"(a[8]), "+f"(a[9]), "+f"(a[10]), "+f"(a[11]), "+f"(a[12]), "+f"(a[13]), "+f"(a[14]), "+f"(a[15])
#define ACC32(a)                                                                                              \
    ACC16(a),                                                                                                 \
    "+f"(a[16]), "+f"(a[17]), "+f"(a[18]), "+f"(a[19]), "+f"(a[20]), "+f"(a[21]), "+f"(a[22]), "+f"(a[23]),   \
    "+f"(a[24]), "+f"(a[25]), "+f"(a[26]), "+f"(a[27]), "+f"(a[28]), "+f"(a[29]), "+f"(a[30]), "+f"(a[31])
#define ACC16_STR "{%0, %1, %2, %3, %4, %5, %6, %7, %8, %9, %10, %11, %12, %13, %14, %15}"
#define ACC32_STR                                                                                             \
    "{%0, %1, %2, %3, %4, %5, %6, %7, %8, %9, %10, %11, %12, %13, %14, %15, "                                 \
    "%16, %17, %18, %19, %20, %21, %22, %23, %24, %25, %26, %27, %28, %29, %30, %31}"

template <int BOFF>
__device__ __forceinline__ void wgmma_rs(float (&d)[32], uint32_t a0, uint32_t a1, uint32_t a2, uint32_t a3, uint32_t db_lo) {
    asm volatile("{\n.reg .b64 db;\n.reg .b32 lo;\n"
                 "add.u32 lo, %36, %37;\nmov.b64 db, {lo, 0x40000040};\n"
                 "wgmma.mma_async.sync.aligned.m64n64k16.f32.bf16.bf16 " ACC32_STR
                 ", {%32, %33, %34, %35}, db, 1, -1, 1, 0;\n}"
                 : ACC32(d) : "r"(a0), "r"(a1), "r"(a2), "r"(a3), "r"(db_lo), "n"(BOFF));
}
template <int ACCUM, int AOFF, int BOFF>
__device__ __forceinline__ void wgmma_ss(float (&d)[32], uint32_t da_lo, uint32_t db_lo) {
    asm volatile("{\n.reg .b64 da, db;\n.reg .b32 lo;\n"
                 "add.u32 lo, %32, %34;\nmov.b64 da, {lo, 0x40000040};\n"
                 "add.u32 lo, %36, %35;\nmov.b64 db, {lo, 0x40000040};\n"
                 "wgmma.mma_async.sync.aligned.m64n64k16.f32.bf16.bf16 " ACC32_STR
                 ", da, db, %33, 1, 1, 1, 0;\n}"
                 : ACC32(d) : "r"(da_lo), "n"(ACCUM), "n"(AOFF), "n"(BOFF), "r"(db_lo));
}
template <int ACCUM, int AOFF, int BOFF>
__device__ __forceinline__ void wgmma_ss32(float (&d)[16], uint32_t da_lo, uint32_t db_lo) {
    asm volatile("{\n.reg .b64 da, db;\n.reg .b32 lo;\n"
                 "add.u32 lo, %16, %18;\nmov.b64 da, {lo, 0x40000040};\n"
                 "add.u32 lo, %20, %19;\nmov.b64 db, {lo, 0x40000040};\n"
                 "wgmma.mma_async.sync.aligned.m64n32k16.f32.bf16.bf16 " ACC16_STR
                 ", da, db, %17, 1, 1, 1, 0;\n}"
                 : ACC16(d) : "r"(da_lo), "n"(ACCUM), "n"(AOFF), "n"(BOFF), "r"(db_lo));
}
__device__ __forceinline__ uint32_t desc_lo(uint32_t addr) { return ((addr & 0x3FFFFu) >> 4) | (1u << 16); }
__device__ __forceinline__ uint32_t pack_bf16(float lo, float hi) {
    uint32_t r;
    asm("cvt.rn.bf16x2.f32 %0, %1, %2;" : "=r"(r) : "f"(hi), "f"(lo));
    return r;
}
__device__ __forceinline__ uint32_t enc_neg(uint32_t pair) {
    const uint32_t v = pair ^ 0x80008000u;
    return v == 0u ? 0x80008000u : v;
}
__device__ __forceinline__ uint32_t pack_neg(float lo, float hi) { return enc_neg(pack_bf16(lo, hi)); }
__device__ __forceinline__ float dup(float x, float one) {
    float r;
    asm volatile("mul.f32 %0, %1, %2;" : "=f"(r) : "f"(x), "f"(one));
    return r;
}
__device__ __forceinline__ void stsm_x4_t(uint32_t addr, uint32_t r0, uint32_t r1, uint32_t r2, uint32_t r3) {
    asm volatile("stmatrix.sync.aligned.m8n8.x4.trans.shared.b16 [%0], {%1, %2, %3, %4};"
                 ::"r"(addr), "r"(r0), "r"(r1), "r"(r2), "r"(r3) : "memory");
}

struct Ctx {
    uint32_t sbase;
    uint32_t db0;
    uint32_t da0;
    uint32_t empty_tgt;
    bool     signal;
};

template <int N> __device__ __forceinline__ constexpr uint32_t slot_of() { return (3 + N) % NSLOTS; }
template <int N> __device__ __forceinline__ uint32_t phase_of(uint32_t pu) { return pu ^ (((3 + N) / NSLOTS) & 1); }
template <int N> __device__ __forceinline__ void release(const Ctx& cx) {
    if (cx.signal) mbar_arrive_cluster(cx.empty_tgt + slot_of<N>() * 8);
}

enum { FINE, COARSE, COARSE_REG };
template <int N, int MODE>
__device__ __forceinline__ void chunk(float (&acc)[32], const uint32_t (&W)[96], const uint32_t (&A)[16], uint32_t zero,
                                      const Ctx& cx, uint32_t pu, bool& ready) {
    constexpr int KC = N % 6;
    constexpr int B  = slot_of<N>() * 512;
    if (!ready) mbar_wait(cx.sbase + OFF_FULL + slot_of<N>() * 8, phase_of<N>(pu));
    ready = mbar_try(cx.sbase + OFF_FULL + slot_of<N + 1>() * 8, phase_of<N + 1>(pu));
    if (MODE == FINE) {
        wg_fence();
        wgmma_rs<B + 0>(acc, W[KC * 16 + 0],  W[KC * 16 + 1],  W[KC * 16 + 2],  W[KC * 16 + 3], cx.db0);
        wgmma_rs<B + 2>(acc, W[KC * 16 + 4],  W[KC * 16 + 5],  W[KC * 16 + 6],  W[KC * 16 + 7], cx.db0);
        wgmma_rs<B + 4>(acc, W[KC * 16 + 8],  W[KC * 16 + 9],  W[KC * 16 + 10], W[KC * 16 + 11], cx.db0);
        wgmma_rs<B + 6>(acc, W[KC * 16 + 12], W[KC * 16 + 13], W[KC * 16 + 14], W[KC * 16 + 15], cx.db0);
    } else {
        if (MODE == COARSE) {
            wg_fence();
            wgmma_ss<(KC > 0), KC * 4 * 128, B>(acc, cx.da0, cx.db0);
        } else {
            uint32_t a[4];
#pragma unroll
            for (int i = 0; i < 4; i++) asm volatile("xor.b32 %0, %1, %2;" : "=r"(a[i]) : "r"(A[((KC + 2) & 3) * 4 + i]), "r"(zero));
            wg_fence();
            wgmma_rs<B>(acc, a[0], a[1], a[2], a[3], cx.db0);
            wg_commit();
        }
        wgmma_ss<1, (KC * 4 + 1) * 128, B + 2>(acc, cx.da0, cx.db0);
        wgmma_ss<1, (KC * 4 + 2) * 128, B + 4>(acc, cx.da0, cx.db0);
        wgmma_ss<1, (KC * 4 + 3) * 128, B + 6>(acc, cx.da0, cx.db0);
    }
    wg_commit();
    if (KC > 0) {
        wg_wait<1>();
        release<N - (KC > 0)>(cx);
    }
}

__device__ __forceinline__ int seg_row(int g) {
    const int y = g / 12;
    return y * (2 * HW) + (g - y * 12) * 32;
}

template <int NP>
__global__ void __cluster_dims__(2, 1, 1) __launch_bounds__(NTHREADS, 1)
fpn_kernel(Scratch* scr,
           const __nv_bfloat16* __restrict__ c_ptr, const __nv_bfloat16* __restrict__ p_ptr, const int nsteps, const float one, const uint32_t zero,
           const __grid_constant__ CUtensorMap tm_w64, const __grid_constant__ CUtensorMap tm_wl3,
           const __grid_constant__ CUtensorMap tm_p8, const __grid_constant__ CUtensorMap tm_c,
           const __grid_constant__ CUtensorMap tm_p, const __grid_constant__ CUtensorMap tm_out)
{
    extern __shared__ __align__(1024) uint8_t smem[];
    const uint32_t sbase = smem_u32(smem);
    const int tid   = threadIdx.x;
    const int warp  = __shfl_sync(0xffffffffu, tid >> 5, 0);
    const int lane  = tid & 31;
    const int rank  = blockIdx.x & 1;
    const int pair  = blockIdx.x >> 1;
    const int npair = NP ? NP : gridDim.x >> 1;
    const int nfine = NP ? NSEG / (NP ? NP : 1) : nsteps;

    if (tid == 480) {
        prefetch_tmap(&tm_w64); prefetch_tmap(&tm_wl3); prefetch_tmap(&tm_p8);
        prefetch_tmap(&tm_c); prefetch_tmap(&tm_p); prefetch_tmap(&tm_out);
    }
    if (tid == 384) {
        for (int s = 0; s < 3; s++) mbar_init(sbase + OFF_FULL + s * 8, 1);
        asm volatile("fence.mbarrier_init.release.cluster;" ::: "memory");
        asm volatile("fence.proxy.async.shared::cta;" ::: "memory");
        const int g0 = pair % 3;
#pragma unroll 1
        for (int s = 0; s < 3; s++) {
            const uint32_t bar = sbase + OFF_FULL + s * 8;
            const uint32_t dst = sbase + OFF_WOUT + g0 * WOUT_SLICE + s * 16384;
            mbar_expect_tx(bar, pair < NJOBS ? 3 * SLOT_BYTES : 2 * SLOT_BYTES);
            tma_load_2d(dst, &tm_w64, rank * 192 + g0 * 64, s * 128, bar);
            if (pair < NJOBS) tma_load_3d(sbase + OFF_RING + s * SLOT_BYTES, &tm_wl3, 0, (pair / 3) * 32, 2 * s, bar);
            tma_load_2d(dst + 8192, &tm_w64, rank * 192 + g0 * 64, s * 128 + 64, bar);
        }
    }
    if (warp == 13) {
        if (lane == 0) {
            for (int s = 0; s < NSLOTS; s++) {
                if (s >= 3) mbar_init(sbase + OFF_FULL + s * 8, 1);
                mbar_init(sbase + OFF_EMPTY + s * 8, 6);
            }
            mbar_init(sbase + OFF_JB2, 1);
            asm volatile("st.volatile.shared.u32 [%0], %1;" ::"r"(sbase + OFF_PACE), "r"(6) : "memory");
            asm volatile("fence.mbarrier_init.release.cluster;" ::: "memory");
            asm volatile("fence.proxy.async.shared::cta;" ::: "memory");
        }
        __syncwarp();
        asm volatile("bar.arrive 5, 448;" ::: "memory");
    }
    __syncwarp();
    asm volatile("barrier.cluster.arrive.relaxed.aligned;" ::: "memory");

    if (warp >= 12) {
        asm volatile("setmaxnreg.dec.sync.aligned.u32 32;");
        if (warp == 12) {
            asm volatile("bar.sync 5, 448;" ::: "memory");
            if (lane == 0) {
                const int g1 = (pair + 1) % 3, g2 = (pair + 2) % 3;
#pragma unroll 1
                for (int kc = 0; kc < 6; kc++) {
                    const uint32_t bar = sbase + OFF_FULL + (3 + kc) * 8;
                    mbar_expect_tx(bar, 3 * SLOT_BYTES);
                    tma_load_5d(sbase + OFF_RING + (3 + kc) * SLOT_BYTES, &tm_p8, kc * 64, pair * 2, 0, bar);
                    tma_load_2d(sbase + OFF_WOUT + g1 * WOUT_SLICE + kc * 8192, &tm_w64, rank * 192 + g1 * 64, kc * 64, bar);
                    tma_load_2d(sbase + OFF_WOUT + g2 * WOUT_SLICE + kc * 8192, &tm_w64, rank * 192 + g2 * 64, kc * 64, bar);
                }
            }
            __syncwarp();
        }
        asm volatile("barrier.cluster.wait.aligned;" ::: "memory");
        if (warp == 12) {
            if (lane == 0) {
                const uint32_t dst0 = sbase + OFF_RING + rank * 4096;
                uint32_t so = 9 * 8, ph = 1, step = 6;
                auto acquire = [&](uint32_t& bar, uint32_t& dst) {
                    bar = sbase + OFF_FULL + so;
                    dst = dst0 + so * (SLOT_BYTES / 8);
                    mbar_wait_bounded(sbase + OFF_EMPTY + so, ph);
                    mbar_expect_tx(bar, SLOT_BYTES);
                };
                auto next_slot = [&]() {
                    so += 8;
                    if (so == NSLOTS * 8) { so = 0; ph ^= 1; }
                };
                auto advance = [&]() {
                    next_slot();
                    step++;
                    asm volatile("st.volatile.shared.u32 [%0], %1;" ::"r"(sbase + OFF_PACE), "r"(step) : "memory");
                };
                unsigned mytiles = 0, seen = 0;
                auto look = [&]() {
                    asm volatile("ld.relaxed.gpu.global.u32 %0, [%1];" : "=r"(seen) : "l"(&scr->prog) : "memory");
                };
                auto count = [&]() {
                    asm volatile("red.relaxed.gpu.global.add.u32 [%0], 1;" ::"l"(&scr->prog) : "memory");
                };
                auto govern = [&]() {
                    if (rank == 0) {
                        unsigned spins = 0;
                        const unsigned slack = 2 * max(GOV_TIGHT - (int)mytiles, 0);
                        while (mytiles >= GOV_START && mytiles * npair > seen + slack && ++spins < 100000u) look();
                        mytiles++;
                    }
                };
#pragma unroll 1
                for (int j = 0; j < nfine; j++) {
                    const uint64_t pol = j >= nfine - EF_STEPS ? POLICY_EVICT_FIRST : POLICY_EVICT_NORMAL;
                    if ((j & 3) == 0 && j > 0) {
                        govern();
#pragma unroll
                        for (int kc = 0; kc < 6; kc++) {
                            uint32_t bar, dst;
                            acquire(bar, dst);
                            tma_load_5d_mc(dst, &tm_p, kc * 64, pair * 2, j + 2 * rank, bar, pol);
                            advance();
                            if (kc == 0 && rank == 0) count();
                            if (kc == 3 && rank == 0) look();
                        }
                    }
                    const int row = seg_row(j * npair + pair) + rank * HW;
                    govern();
#pragma unroll
                    for (int kc = 0; kc < 6; kc++) {
                        uint32_t bar, dst;
                        acquire(bar, dst);
                        tma_load_2d_mc(dst, &tm_c, kc * 64, row, bar, pol);
                        advance();
                        if (kc == 0 && rank == 0 && j + 1 < nfine) count();
                        if (kc == 3 && rank == 0) look();
                    }
                }
                if (rank == 0) {
                    if (atomicAdd(&scr->prog, 1u) + 1 == mytiles * npair) {
                        asm volatile("st.relaxed.gpu.global.u32 [%0], 0;" ::"l"(&scr->prog) : "memory");
                        asm volatile("red.relaxed.gpu.global.add.u32 [%0], 1;" ::"l"(&scr->epoch) : "memory");
                    }
                }
                for (int s = 0; s < NSLOTS; s++) {
                    mbar_wait_bounded(sbase + OFF_EMPTY + so, ph);
                    next_slot();
                }
            }
        } else if (warp == 13) {
#pragma unroll 1
            for (int i = PF_START; i < nfine + nfine / 4; i++) {
                const int k5 = i / 5, t = i - k5 * 5;
                const char *b0, *b1;
                if (t == 0) {
                    b0 = (const char*)p_ptr + (size_t)((4 * k5 + 2 * rank) * npair + pair) * (16 * C * 2);
                    b1 = b0 + (size_t)npair * (16 * C * 2);
                } else {
                    b0 = (const char*)c_ptr + (size_t)(seg_row((4 * k5 + t - 1) * npair + pair) + rank * HW) * (C * 2);
                    b1 = b0 + 16 * C * 2;
                }
                const int need = max(6 * i - max(PF_LEAD0 - max(i - PF_DECAY, 0), PF_LEAD), PF_FIRST);
                unsigned spins = 0;
                while (true) {
                    uint32_t v;
                    asm volatile("ld.volatile.shared.u32 %0, [%1];" : "=r"(v) : "r"(sbase + OFF_PACE) : "memory");
                    if ((int)v >= need || ++spins > 4000000u) break;
                    __nanosleep(20);
                }
#pragma unroll
                for (int k = 0; k < 6; k++) {
                    asm volatile("prefetch.global.L2 [%0];" ::"l"((k < 3 ? b0 : b1) + lane * 128 + (k % 3) * 4096) : "memory");
                    __nanosleep(i < PF_START + 2 ? PF_GAP0 : PF_GAP);
                }
            }
        } else if (warp == 15) {
            uint32_t par, v;
            asm volatile("ld.relaxed.gpu.global.u32 %0, [%1];" : "=r"(par) : "l"(&scr->epoch) : "memory");
            uint4* clr = scr->wfrag + (~par & 1) * (6 * NFRAG * 128);
            unsigned spins = 0;
            do {
                __nanosleep(500);
                asm volatile("ld.volatile.shared.u32 %0, [%1];" : "=r"(v) : "r"(sbase + OFF_PACE) : "memory");
            } while (v < CLR_AT && ++spins < 100000u);
            for (int i = blockIdx.x * 32 + lane; i < 6 * NFRAG * 128; i += npair * 64) clr[i] = make_uint4(0u, 0u, 0u, 0u);
        }
    } else {
        uint32_t par;
        asm volatile("ld.relaxed.gpu.global.u32 %0, [%1];" : "=r"(par) : "l"(&scr->epoch) : "memory");
        asm volatile("setmaxnreg.inc.sync.aligned.u32 160;");
        asm volatile("bar.sync 5, 448;" ::: "memory");
        const int wg   = warp >> 2;
        const int wtid = tid & 127;
        Ctx cx;
        cx.sbase     = sbase;
        cx.empty_tgt = mapa(sbase + OFF_EMPTY, warp & 1);
        cx.signal    = (lane == 0) && ((warp & 3) < 2);
        cx.db0       = desc_lo(sbase + OFF_RING);
        cx.da0       = desc_lo(sbase + OFF_WOUT + wg * WOUT_SLICE);
        const int cb = rank * 3 + wg;

        float    acc[32];
        uint32_t qp[16];
        uint32_t W[96];

        {
            uint32_t jph = 0;
            for (int job = pair; job < NJOBS; job += npair) {
                if (job % 3 == wg) {
                    if (job != pair) {
                        named_bar(wg);
                        if (wtid == 0) {
                            mbar_expect_tx(sbase + OFF_JB2, 6 * 4096);
                            for (int s = 0; s < 3; s++)
                                tma_load_3d(sbase + OFF_RING + s * SLOT_BYTES, &tm_wl3, 0, (job / 3) * 32, 2 * s, sbase + OFF_JB2);
                        }
                        for (int kc = 0; kc < 6; kc++) mbar_wait(sbase + OFF_FULL + (3 + kc) * 8, 0);
                        mbar_wait(sbase + OFF_JB2, jph);
                    }
                    float ja[16];
#define JOBK(k) wgmma_ss32<((k) > 0), (k) * 128, ((k) >> 2) * 256 + ((k) & 3) * 2>(ja, cx.da0, cx.db0);
                    mbar_wait(sbase + OFF_FULL, 0);
                    wg_fence();
                    JOBK(0)  JOBK(1)  JOBK(2)  JOBK(3)  JOBK(4)  JOBK(5)  JOBK(6)  JOBK(7)
                    wg_commit();
                    mbar_wait(sbase + OFF_FULL + 8, 0);
                    wg_fence();
                    JOBK(8)  JOBK(9)  JOBK(10) JOBK(11) JOBK(12) JOBK(13) JOBK(14) JOBK(15)
                    wg_commit();
                    mbar_wait(sbase + OFF_FULL + 16, 0);
                    wg_fence();
                    JOBK(16) JOBK(17) JOBK(18) JOBK(19) JOBK(20) JOBK(21) JOBK(22) JOBK(23)
#undef JOBK
                    wg_commit();
                    wg_wait<0>();
                    const int fidx = (cb * NFRAG + (job / 3) * 2) * 128 + wtid;
                    uint4* dst = scr->wfrag + (par & 1) * (6 * NFRAG * 128) + fidx;
#pragma unroll
                    for (int i = 0; i < 2; i++) {
                        asm volatile("st.relaxed.gpu.global.v4.u32 [%0], {%1, %2, %3, %4};" ::"l"(dst + i * 128),
                                     "r"(pack_neg(ja[8 * i + 0], ja[8 * i + 1])), "r"(pack_neg(ja[8 * i + 2], ja[8 * i + 3])),
                                     "r"(pack_neg(ja[8 * i + 4], ja[8 * i + 5])), "r"(pack_neg(ja[8 * i + 6], ja[8 * i + 7])) : "memory");
                    }
                }
                if (job + npair < NJOBS) asm volatile("bar.sync 4, 384;" ::: "memory");
                if (job != pair) jph ^= 1;
            }
        }

        par &= 1;
        if (pair < NJOBS) asm volatile("bar.sync 6, 384;" ::: "memory");
        asm volatile("barrier.cluster.wait.aligned;" ::: "memory");

        mbar_wait(sbase + OFF_FULL, 0);
        mbar_wait(sbase + OFF_FULL + 8, 0);
        mbar_wait(sbase + OFF_FULL + 16, 0);
        if (cx.signal) {
            mbar_arrive_cluster(cx.empty_tgt);
            mbar_arrive_cluster(cx.empty_tgt + 8);
            mbar_arrive_cluster(cx.empty_tgt + 16);
        }
        auto pack_q = [&]() {
            uint32_t all = 0;
#pragma unroll
            for (int i = 0; i < 16; i++) {
                qp[i] = pack_bf16(acc[2 * i], acc[2 * i + 1]);
                if (i >= 4) all |= qp[i];
            }
            qp[3] |= all & zero;
        };
        bool ready = false;
        uint32_t pu = 0;
#define CHUNK(N, MODE) chunk<N, MODE>(acc, W, qp, zero, cx, pu, ready)

        const uint4* wsrc = scr->wfrag + (par * 6 + cb) * (NFRAG * 128) + wtid;
        auto load_w = [&](int kc) {
#pragma unroll
            for (int s = 4 * kc; s < 4 * kc + 4; s++) {
                asm volatile("ld.relaxed.gpu.global.v4.u32 {%0, %1, %2, %3}, [%4];"
                             : "=r"(W[4 * s]), "=r"(W[4 * s + 1]), "=r"(W[4 * s + 2]), "=r"(W[4 * s + 3])
                             : "l"(wsrc + s * 128) : "memory");
            }
        };
        auto check_w = [&](int kc) {
            uint32_t* w = kc < 6 ? W + 16 * kc : qp;
            asm volatile(
                "{\n.reg .pred p;\n.reg .u32 m, n;\n"
                "mov.u32 n, 0;\n"
                "CHK_%=:\n"
                "mov.u32 m, %%clock;\n or.b32 m, m, 1;\n min.u32 m, m, %0;\n"
                "min.u32 m, m, %1;\n min.u32 m, m, %2;\n min.u32 m, m, %3;\n min.u32 m, m, %4;\n min.u32 m, m, %5;\n"
                "min.u32 m, m, %6;\n min.u32 m, m, %7;\n min.u32 m, m, %8;\n min.u32 m, m, %9;\n min.u32 m, m, %10;\n"
                "min.u32 m, m, %11;\n min.u32 m, m, %12;\n min.u32 m, m, %13;\n min.u32 m, m, %14;\n min.u32 m, m, %15;\n"
                "setp.ne.u32 p, m, 0;\n"
                "vote.sync.all.pred p, p, 0xffffffff;\n"
                "@p bra.uni OK_%=;\n"
                "add.u32 n, n, 1;\n"
                "setp.gt.u32 p, n, 5000000;\n"
                "@p bra.uni OK_%=;\n"
                "ld.relaxed.gpu.global.v4.u32 {%0, %1, %2, %3}, [%16];\n"
                "ld.relaxed.gpu.global.v4.u32 {%4, %5, %6, %7}, [%16 + 2048];\n"
                "ld.relaxed.gpu.global.v4.u32 {%8, %9, %10, %11}, [%16 + 4096];\n"
                "ld.relaxed.gpu.global.v4.u32 {%12, %13, %14, %15}, [%16 + 6144];\n"
                "bra.uni CHK_%=;\n"
                "OK_%=:\n}"
                : "+r"(w[0]), "+r"(w[1]), "+r"(w[2]), "+r"(w[3]), "+r"(w[4]), "+r"(w[5]), "+r"(w[6]), "+r"(w[7]),
                  "+r"(w[8]), "+r"(w[9]), "+r"(w[10]), "+r"(w[11]), "+r"(w[12]), "+r"(w[13]), "+r"(w[14]), "+r"(w[15])
                : "l"(wsrc + kc * 512) : "memory");
        };
        const uint32_t stage = sbase + OFF_WOUT + wg * WOUT_SLICE + 2 * 8192;
        const uint32_t st_addr = stage + (((lane >> 4) * 8 + (lane & 7)) << 7)
                               + (((((warp & 3) << 1) | ((lane >> 3) & 1)) ^ (lane & 7)) << 4);
        auto publish = [&](int s) {
            if (pair == (NJOBS + s) % npair) {
                uint32_t a[4];
                asm volatile("ldmatrix.sync.aligned.m8n8.x4.trans.shared.b16 {%0, %1, %2, %3}, [%4];"
                             : "=r"(a[0]), "=r"(a[1]), "=r"(a[2]), "=r"(a[3]) : "r"(st_addr + s * 8192) : "memory");
                asm volatile("st.relaxed.gpu.global.v4.u32 [%0], {%1, %2, %3, %4};" ::"l"(wsrc + (24 + s) * 128),
                             "r"(enc_neg(a[0])), "r"(enc_neg(a[1])), "r"(enc_neg(a[2])), "r"(enc_neg(a[3])) : "memory");
            }
        };
        CHUNK(0, COARSE);
        CHUNK(1, COARSE);
        CHUNK(2, COARSE);
        publish(0);
        load_w(0);
        CHUNK(3, COARSE);
        publish(1);
        load_w(1);
        CHUNK(4, COARSE);
        publish(2);
        load_w(2);
        CHUNK(5, COARSE);
        publish(3);
        wg_wait<0>();
        release<5>(cx);
        pack_q();

        auto flush_part = [&](int row, int part) {
            if (part == 0) {
                asm volatile("fence.proxy.async.shared::cta;" ::: "memory");
                named_bar(wg);
            }
            if (wtid == 0) {
                tma_store_2d(&tm_out, cb * 64, row + (part >> 1) * HW + (part & 1) * 16, stage + part * 8192, POLICY_EVICT_FIRST);
                if (part == 3) asm volatile("cp.async.bulk.commit_group;" ::: "memory");
            }
        };
        auto init_acc = [&](int t) {
#pragma unroll
            for (int b = 0; b < 2; b++) {
#pragma unroll
                for (int h = 0; h < 2; h++) {
                    const uint32_t q = qp[t * 4 + b * 2 + h];
                    const float lo = __uint_as_float(q << 16), hi = __uint_as_float(q & 0xffff0000u);
#pragma unroll
                    for (int dy = 0; dy < 2; dy++) {
                        acc[16 * dy + 8 * b + 2 * h]         = dy ? dup(lo, one) : lo;
                        acc[16 * dy + 8 * b + 2 * h + 1]     = dup(lo, one);
                        acc[16 * dy + 8 * b + 4 + 2 * h]     = dy ? dup(hi, one) : hi;
                        acc[16 * dy + 8 * b + 4 + 2 * h + 1] = dup(hi, one);
                    }
                }
            }
        };
        auto stage_tile = [&](int slot) {
            if (wtid == 0) asm volatile("cp.async.bulk.wait_group.read 0;" ::: "memory");
            named_bar(wg);
            wg_wait<0>();
            if (cx.signal) mbar_arrive_cluster(cx.empty_tgt + slot * 8);
#pragma unroll
            for (int i = 0; i < 8; i += 2) {
                stsm_x4_t(st_addr + i * 4096,
                          pack_bf16(acc[4 * i + 0], acc[4 * i + 1]), pack_bf16(acc[4 * i + 2], acc[4 * i + 3]),
                          pack_bf16(acc[4 * i + 4], acc[4 * i + 5]), pack_bf16(acc[4 * i + 6], acc[4 * i + 7]));
            }
        };

        auto load_wo = [&]() {
#pragma unroll
            for (int s = 0; s < 4; s++) {
                asm volatile("ld.global.ca.v4.u32 {%0, %1, %2, %3}, [%4];"
                             : "=r"(qp[4 * s]), "=r"(qp[4 * s + 1]), "=r"(qp[4 * s + 2]), "=r"(qp[4 * s + 3])
                             : "l"(wsrc + (24 + s) * 128) : "memory");
            }
        };

        init_acc(0);
        check_w(0);
        load_w(3);
        load_w(4);
        CHUNK(6, FINE);
        check_w(1);
        CHUNK(7, FINE);
        check_w(2);
        CHUNK(8, FINE);
        check_w(3);
        load_w(5);
        CHUNK(9, FINE);
        check_w(4);
        CHUNK(10, FINE);
        check_w(5);
        CHUNK(11, FINE);

        int seg = pair;
        int prow = seg_row(seg);
        while (true) {
            stage_tile(slot_of<11>());
            init_acc(1);
            CHUNK(12, FINE);
            flush_part(prow, 0);
            CHUNK(13, FINE);
            CHUNK(14, FINE);
            flush_part(prow, 1);
            CHUNK(15, FINE);
            flush_part(prow, 2);
            CHUNK(16, FINE);
            flush_part(prow, 3);
            CHUNK(17, FINE);
            seg += npair;
            prow = seg_row(seg);
            stage_tile(slot_of<17>());
            init_acc(2);
            CHUNK(18, FINE);
            flush_part(prow, 0);
            CHUNK(19, FINE);
            CHUNK(20, FINE);
            flush_part(prow, 1);
            CHUNK(21, FINE);
            flush_part(prow, 2);
            CHUNK(22, FINE);
            flush_part(prow, 3);
            CHUNK(23, FINE);
            seg += npair;
            prow = seg_row(seg);
            stage_tile(slot_of<23>());
            init_acc(3);
            CHUNK(24, FINE);
            flush_part(prow, 0);
            CHUNK(25, FINE);
            load_wo();
            CHUNK(26, FINE);
            flush_part(prow, 1);
            CHUNK(27, FINE);
            flush_part(prow, 2);
            CHUNK(28, FINE);
            flush_part(prow, 3);
            CHUNK(29, FINE);
            seg += npair;
            prow = seg_row(seg);
            if (seg + npair >= NSEG) break;
            stage_tile(slot_of<29>());
            CHUNK(30, COARSE);
            flush_part(prow, 0);
            CHUNK(31, COARSE);
            check_w(6);
            CHUNK(32, COARSE_REG);
            CHUNK(33, COARSE_REG);
            flush_part(prow, 1);
            CHUNK(34, COARSE_REG);
            CHUNK(35, COARSE_REG);
            wg_wait<0>();
            release<35>(cx);
            pack_q();
            init_acc(0);
            CHUNK(36, FINE);
            flush_part(prow, 2);
            CHUNK(37, FINE);
            CHUNK(38, FINE);
            CHUNK(39, FINE);
            flush_part(prow, 3);
            CHUNK(40, FINE);
            CHUNK(41, FINE);
            seg += npair;
            prow = seg_row(seg);
            pu ^= 1;
        }
#undef CHUNK
        stage_tile(slot_of<29>());
#pragma unroll
        for (int part = 0; part < 4; part++) flush_part(prow, part);
        if (wtid == 0) asm volatile("cp.async.bulk.wait_group.read 0;" ::: "memory");
    }
}

typedef CUresult (*EncodeFn)(CUtensorMap*, CUtensorMapDataType, cuuint32_t, void*, const cuuint64_t*, const cuuint64_t*,
                             const cuuint32_t*, const cuuint32_t*, CUtensorMapInterleave, CUtensorMapSwizzle,
                             CUtensorMapL2promotion, CUtensorMapFloatOOBfill);

void encode(EncodeFn fn, CUtensorMap* tm, const void* ptr, int rank, const cuuint64_t* dims, const cuuint64_t* strides,
            const cuuint32_t* box) {
    const cuuint32_t es[5] = {1, 1, 1, 1, 1};
    fn(tm, CU_TENSOR_MAP_DATA_TYPE_BFLOAT16, (cuuint32_t)rank, const_cast<void*>(ptr), dims, strides, box, es,
       CU_TENSOR_MAP_INTERLEAVE_NONE, CU_TENSOR_MAP_SWIZZLE_128B, CU_TENSOR_MAP_L2_PROMOTION_NONE,
       CU_TENSOR_MAP_FLOAT_OOB_FILL_NONE);
}

}

extern "C" void kernel_launch(void* const* d_in, const int* in_sizes, int n_in, void* d_out, int out_size) {
    (void)in_sizes; (void)n_in; (void)out_size;
    const __nv_bfloat16* c_fine   = (const __nv_bfloat16*)d_in[0];
    const __nv_bfloat16* p_coarse = (const __nv_bfloat16*)d_in[1];
    const __nv_bfloat16* w_lat    = (const __nv_bfloat16*)d_in[2];
    const __nv_bfloat16* w_out    = (const __nv_bfloat16*)d_in[3];

    static EncodeFn fn = nullptr;
    static int np = 0;
    static Scratch* scr = nullptr;
    if (!fn) {
        void* p = nullptr;
        cudaDriverEntryPointQueryResult qr;
        cudaGetDriverEntryPoint("cuTensorMapEncodeTiled", &p, cudaEnableDefault, &qr);
        fn = (EncodeFn)p;
        cudaGetSymbolAddress((void**)&scr, g_scratch);
        cudaFuncSetAttribute(fpn_kernel<NPAIRS>, cudaFuncAttributeMaxDynamicSharedMemorySize, SMEM_BYTES);
        cudaFuncSetAttribute(fpn_kernel<0>, cudaFuncAttributeMaxDynamicSharedMemorySize, SMEM_BYTES);
        cudaLaunchConfig_t cfg = {};
        cfg.gridDim = dim3(2); cfg.blockDim = dim3(NTHREADS); cfg.dynamicSmemBytes = SMEM_BYTES;
        cudaLaunchAttribute at[1];
        at[0].id = cudaLaunchAttributeClusterDimension;
        at[0].val.clusterDim.x = 2; at[0].val.clusterDim.y = 1; at[0].val.clusterDim.z = 1;
        cfg.attrs = at; cfg.numAttrs = 1;
        if (cudaOccupancyMaxActiveClusters(&np, fpn_kernel<0>, &cfg) != cudaSuccess || np < 1) np = 1;
        if (np > NPAIRS) np = NPAIRS;
        while ((NSEG / 4) % np) np--;
    }

    CUtensorMap tm_c, tm_p, tm_wl3, tm_out, tm_p8, tm_w64;
    {
        const cuuint64_t dims[2] = {(cuuint64_t)C, (cuuint64_t)NPIX};
        const cuuint64_t str[1]  = {(cuuint64_t)C * 2};
        const cuuint32_t box_in[2]  = {64, 32};
        const cuuint32_t box_out[2] = {64, 16};
        encode(fn, &tm_c, c_fine, 2, dims, str, box_in);
        encode(fn, &tm_out, d_out, 2, dims, str, box_out);
    }
    {
        const cuuint64_t dims[5] = {(cuuint64_t)C, 2, 4, (cuuint64_t)(2 * np), (cuuint64_t)(NSEG / np)};
        const cuuint64_t str[4]  = {(cuuint64_t)4 * C * 2, (cuuint64_t)C * 2, (cuuint64_t)8 * C * 2, (cuuint64_t)np * 16 * C * 2};
        const cuuint32_t box[5]  = {64, 2, 4, 2, 2};
        encode(fn, &tm_p, p_coarse, 5, dims, str, box);
        const cuuint32_t box8[5] = {64, 2, 4, 2, 4};
        encode(fn, &tm_p8, p_coarse, 5, dims, str, box8);
    }
    {
        const cuuint64_t dims[2] = {(cuuint64_t)C, (cuuint64_t)C};
        const cuuint64_t str[1]  = {(cuuint64_t)C * 2};
        const cuuint32_t box_k[2] = {64, 64};
        encode(fn, &tm_w64, w_out, 2, dims, str, box_k);
    }
    {
        const cuuint64_t dims[3] = {64, (cuuint64_t)C, 6};
        const cuuint64_t str[2]  = {(cuuint64_t)C * 2, 128};
        const cuuint32_t box[3]  = {64, 32, 2};
        encode(fn, &tm_wl3, w_lat, 3, dims, str, box);
    }
    auto kernel = np == NPAIRS ? fpn_kernel<NPAIRS> : fpn_kernel<0>;
    kernel<<<2 * np, NTHREADS, SMEM_BYTES>>>(scr, c_fine, p_coarse, NSEG / np, 1.0f, 0u,
                                             tm_w64, tm_wl3, tm_p8, tm_c, tm_p, tm_out);
}
```

```cpp
#include <cuda_runtime.h>
#include <cuda_bf16.h>
#include <cuda.h>
#include <stdint.h>

namespace {

constexpr int C          = 384;
constexpr int HW         = 384;
constexpr int NPIX       = HW * HW;
constexpr int NSEG       = NPIX / 64;
constexpr int NJOBS      = 36;

constexpr int NFRAG      = 28;
constexpr int NSLOTS     = 10;
constexpr int NPAIRS     = 64;
constexpr int PF_LEAD    = 5;
constexpr int PF_LEAD0   = 18;
constexpr int PF_DECAY   = 11;
constexpr int PF_START   = 3;
constexpr int PF_FIRST   = 11;
constexpr int PF_GAP     = 50;
constexpr int PF_GAP0    = 150;
constexpr int GOV_START  = 10;
constexpr int GOV_TIGHT  = 24;
constexpr int EF_STEPS   = 10;
constexpr int CLR_AT     = 20;

constexpr int SLOT_BYTES  = 8192;
constexpr int WOUT_SLICE  = 384 * 128;
constexpr int OFF_WOUT    = 0;
constexpr int OFF_RING    = 3 * WOUT_SLICE;
constexpr int OFF_FULL    = OFF_RING + NSLOTS * SLOT_BYTES;
constexpr int OFF_EMPTY   = OFF_FULL + 8 * NSLOTS;
constexpr int OFF_JB2     = OFF_EMPTY + 8 * NSLOTS;
constexpr int OFF_PACE    = OFF_JB2 + 8;
constexpr int SMEM_BYTES  = OFF_PACE + 8;
static_assert(SMEM_BYTES <= 232448, "smem");
static_assert(NSLOTS >= 10, "the first tile (nine ring items) is requested in the prologue");


constexpr int NTHREADS = 512;
constexpr uint64_t POLICY_EVICT_FIRST  = 0x12F0000000000000ull;
constexpr uint64_t POLICY_EVICT_NORMAL = 0x1000000000000000ull;

struct Scratch {
    uint4    wfrag[2 * 6 * NFRAG * 128];
    unsigned epoch;
    unsigned pad0[31];
    unsigned prog;
};
__device__ Scratch g_scratch;

__device__ __forceinline__ uint32_t smem_u32(const void* p) { return (uint32_t)__cvta_generic_to_shared(p); }

__device__ __forceinline__ void mbar_init(uint32_t bar, uint32_t cnt) {
    asm volatile("mbarrier.init.shared::cta.b64 [%0], %1;" ::"r"(bar), "r"(cnt) : "memory");
}
__device__ __forceinline__ void mbar_expect_tx(uint32_t bar, uint32_t bytes) {
    asm volatile("mbarrier.arrive.expect_tx.shared::cta.b64 _, [%0], %1;" ::"r"(bar), "r"(bytes) : "memory");
}
__device__ __forceinline__ void mbar_wait_bounded(uint32_t bar, uint32_t parity) {
    asm volatile(
        "{\n"
        ".reg .pred p;\n"
        ".reg .u32 n;\n"
        "mbarrier.try_wait.parity.shared::cta.b64 p, [%0], %1;\n"
        "@p bra DONE_%=;\n"
        "mov.u32 n, 0;\n"
        "WAIT_%=:\n"
        "mbarrier.try_wait.parity.shared::cta.b64 p, [%0], %1;\n"
        "@p bra DONE_%=;\n"
        "add.u32 n, n, 1;\n"
        "setp.lt.u32 p, n, 4000000;\n"
        "@p bra WAIT_%=;\n"
        "trap;\n"
        "DONE_%=:\n"
        "}\n" ::"r"(bar), "r"(parity) : "memory");
}
__device__ __forceinline__ void mbar_wait(uint32_t bar, uint32_t parity) {
    asm volatile(
        "{\n"
        ".reg .pred p;\n"
        "WAIT_%=:\n"
        "mbarrier.try_wait.parity.shared::cta.b64 p, [%0], %1;\n"
        "@!p bra WAIT_%=;\n"
        "}\n" ::"r"(bar), "r"(parity) : "memory");
}
__device__ __forceinline__ bool mbar_try(uint32_t bar, uint32_t parity) {
    uint32_t r;
    asm volatile("{\n.reg .pred p;\nmbarrier.test_wait.parity.shared::cta.b64 p, [%1], %2;\nselp.u32 %0, 1, 0, p;\n}\n"
                 : "=r"(r) : "r"(bar), "r"(parity) : "memory");
    return r != 0;
}
__device__ __forceinline__ void mbar_arrive_cluster(uint32_t cluster_addr) {
    asm volatile("mbarrier.arrive.shared::cluster.b64 _, [%0];" ::"r"(cluster_addr) : "memory");
}
__device__ __forceinline__ uint32_t mapa(uint32_t addr, uint32_t rank) {
    uint32_t r;
    asm("mapa.shared::cluster.u32 %0, %1, %2;" : "=r"(r) : "r"(addr), "r"(rank));
    return r;
}
__device__ __forceinline__ void named_bar(int wg) {
    asm volatile("bar.sync %0, 128;" ::"r"(wg + 1) : "memory");
}

__device__ __forceinline__ void tma_load_2d(uint32_t dst, const CUtensorMap* tm, int c0, int c1, uint32_t bar) {
    asm volatile("cp.async.bulk.tensor.2d.shared::cluster.global.mbarrier::complete_tx::bytes [%0], [%1, {%2, %3}], [%4];"
                 ::"r"(dst), "l"(tm), "r"(c0), "r"(c1), "r"(bar) : "memory");
}
__device__ __forceinline__ void tma_load_3d(uint32_t dst, const CUtensorMap* tm, int c0, int c1, int c2, uint32_t bar) {
    asm volatile("cp.async.bulk.tensor.3d.shared::cluster.global.mbarrier::complete_tx::bytes [%0], [%1, {%2, %3, %4}], [%5];"
                 ::"r"(dst), "l"(tm), "r"(c0), "r"(c1), "r"(c2), "r"(bar) : "memory");
}
__device__ __forceinline__ void tma_load_5d(uint32_t dst, const CUtensorMap* tm, int c0, int c3, int c4, uint32_t bar) {
    asm volatile("cp.async.bulk.tensor.5d.shared::cluster.global.mbarrier::complete_tx::bytes [%0], [%1, {%2, 0, 0, %3, %4}], [%5];"
                 ::"r"(dst), "l"(tm), "r"(c0), "r"(c3), "r"(c4), "r"(bar) : "memory");
}
__device__ __forceinline__ void tma_load_2d_mc(uint32_t dst, const CUtensorMap* tm, int c0, int c1, uint32_t bar, uint64_t pol) {
    asm volatile("cp.async.bulk.tensor.2d.shared::cluster.global.mbarrier::complete_tx::bytes.multicast::cluster.L2::cache_hint"
                 " [%0], [%1, {%2, %3}], [%4], %5, %6;"
                 ::"r"(dst), "l"(tm), "r"(c0), "r"(c1), "r"(bar), "h"((uint16_t)3), "l"(pol) : "memory");
}
__device__ __forceinline__ void tma_load_5d_mc(uint32_t dst, const CUtensorMap* tm, int c0, int c3, int c4, uint32_t bar, uint64_t pol) {
    asm volatile("cp.async.bulk.tensor.5d.shared::cluster.global.mbarrier::complete_tx::bytes.multicast::cluster.L2::cache_hint"
                 " [%0], [%1, {%2, 0, 0, %3, %4}], [%5], %6, %7;"
                 ::"r"(dst), "l"(tm), "r"(c0), "r"(c3), "r"(c4), "r"(bar), "h"((uint16_t)3), "l"(pol) : "memory");
}
__device__ __forceinline__ void tma_store_2d(const CUtensorMap* tm, int c0, int c1, uint32_t src, uint64_t pol) {
    asm volatile("cp.async.bulk.tensor.2d.global.shared::cta.bulk_group.L2::cache_hint [%0, {%1, %2}], [%3], %4;"
                 ::"l"(tm), "r"(c0), "r"(c1), "r"(src), "l"(pol) : "memory");
}
__device__ __forceinline__ bool elect_one() {
    uint32_t r;
    asm volatile("{\n.reg .pred p;\nelect.sync _|p, 0xffffffff;\nselp.u32 %0, 1, 0, p;\n}" : "=r"(r));
    return r != 0;
}
__device__ __forceinline__ void prefetch_tmap(const CUtensorMap* tm) {
    asm volatile("prefetch.tensormap [%0];" ::"l"(tm) : "memory");
}

__device__ __forceinline__ void wg_fence()  { asm volatile("wgmma.fence.sync.aligned;" ::: "memory"); }
__device__ __forceinline__ void wg_commit() { asm volatile("wgmma.commit_group.sync.aligned;" ::: "memory"); }
template <int N> __device__ __forceinline__ void wg_wait() { asm volatile("wgmma.wait_group.sync.aligned %0;" ::"n"(N) : "memory"); }

#define ACC16(a)                                                                                              \
    "+f"(a[0]), "+f"(a[1]), "+f"(a[2]), "+f"(a[3]), "+f"(a[4]), "+f"(a[5]), "+f"(a[6]), "+f"(a[7]),           \
    "+f"(a[8]), "+f"(a[9]), "+f"(a[10]), "+f"(a[11]), "+f"(a[12]), "+f"(a[13]), "+f"(a[14]), "+f"(a[15])
#define ACC32(a)                                                                                              \
    ACC16(a),                                                                                                 \
    "+f"(a[16]), "+f"(a[17]), "+f"(a[18]), "+f"(a[19]), "+f"(a[20]), "+f"(a[21]), "+f"(a[22]), "+f"(a[23]),   \
    "+f"(a[24]), "+f"(a[25]), "+f"(a[26]), "+f"(a[27]), "+f"(a[28]), "+f"(a[29]), "+f"(a[30]), "+f"(a[31])
#define ACC16_STR "{%0, %1, %2, %3, %4, %5, %6, %7, %8, %9, %10, %11, %12, %13, %14, %15}"
#define ACC32_STR                                                                                             \
    "{%0, %1, %2, %3, %4, %5, %6, %7, %8, %9, %10, %11, %12, %13, %14, %15, "                                 \
    "%16, %17, %18, %19, %20, %21, %22, %23, %24, %25, %26, %27, %28, %29, %30, %31}"

template <int BOFF>
__device__ __forceinline__ void wgmma_rs(float (&d)[32], uint32_t a0, uint32_t a1, uint32_t a2, uint32_t a3, uint32_t db_lo) {
    asm volatile("{\n.reg .b64 db;\n.reg .b32 lo;\n"
                 "add.u32 lo, %36, %37;\nmov.b64 db, {lo, 0x40000040};\n"
                 "wgmma.mma_async.sync.aligned.m64n64k16.f32.bf16.bf16 " ACC32_STR
                 ", {%32, %33, %34, %35}, db, 1, -1, 1, 0;\n}"
                 : ACC32(d) : "r"(a0), "r"(a1), "r"(a2), "r"(a3), "r"(db_lo), "n"(BOFF));
}
template <int ACCUM, int AOFF, int BOFF>
__device__ __forceinline__ void wgmma_ss(float (&d)[32], uint32_t da_lo, uint32_t db_lo) {
    asm volatile("{\n.reg .b64 da, db;\n.reg .b32 lo;\n"
                 "add.u32 lo, %32, %34;\nmov.b64 da, {lo, 0x40000040};\n"
                 "add.u32 lo, %36, %35;\nmov.b64 db, {lo, 0x40000040};\n"
                 "wgmma.mma_async.sync.aligned.m64n64k16.f32.bf16.bf16 " ACC32_STR
                 ", da, db, %33, 1, 1, 1, 0;\n}"
                 : ACC32(d) : "r"(da_lo), "n"(ACCUM), "n"(AOFF), "n"(BOFF), "r"(db_lo));
}
template <int ACCUM, int AOFF, int BOFF>
__device__ __forceinline__ void wgmma_ss32(float (&d)[16], uint32_t da_lo, uint32_t db_lo) {
    asm volatile("{\n.reg .b64 da, db;\n.reg .b32 lo;\n"
                 "add.u32 lo, %16, %18;\nmov.b64 da, {lo, 0x40000040};\n"
                 "add.u32 lo, %20, %19;\nmov.b64 db, {lo, 0x40000040};\n"
                 "wgmma.mma_async.sync.aligned.m64n32k16.f32.bf16.bf16 " ACC16_STR
                 ", da, db, %17, 1, 1, 1, 0;\n}"
                 : ACC16(d) : "r"(da_lo), "n"(ACCUM), "n"(AOFF), "n"(BOFF), "r"(db_lo));
}
__device__ __forceinline__ uint32_t desc_lo(uint32_t addr) { return ((addr & 0x3FFFFu) >> 4) | (1u << 16); }
__device__ __forceinline__ uint32_t pack_bf16(float lo, float hi) {
    uint32_t r;
    asm("cvt.rn.bf16x2.f32 %0, %1, %2;" : "=r"(r) : "f"(hi), "f"(lo));
    return r;
}
__device__ __forceinline__ uint32_t enc_neg(uint32_t pair) {
    const uint32_t v = pair ^ 0x80008000u;
    return v == 0u ? 0x80008000u : v;
}
__device__ __forceinline__ uint32_t pack_neg(float lo, float hi) { return enc_neg(pack_bf16(lo, hi)); }
__device__ __forceinline__ float dup(float x, float one) {
    float r;
    asm volatile("mul.f32 %0, %1, %2;" : "=f"(r) : "f"(x), "f"(one));
    return r;
}
__device__ __forceinline__ void stsm_x4_t(uint32_t addr, uint32_t r0, uint32_t r1, uint32_t r2, uint32_t r3) {
    asm volatile("stmatrix.sync.aligned.m8n8.x4.trans.shared.b16 [%0], {%1, %2, %3, %4};"
                 ::"r"(addr), "r"(r0), "r"(r1), "r"(r2), "r"(r3) : "memory");
}

struct Ctx {
    uint32_t sbase;
    uint32_t db0;
    uint32_t da0;
    uint32_t empty_tgt;
    bool     signal;
};

template <int N> __device__ __forceinline__ constexpr uint32_t slot_of() { return (3 + N) % NSLOTS; }
template <int N> __device__ __forceinline__ uint32_t phase_of(uint32_t pu) { return pu ^ (((3 + N) / NSLOTS) & 1); }
template <int N> __device__ __forceinline__ void release(const Ctx& cx) {
    if (cx.signal) mbar_arrive_cluster(cx.empty_tgt + slot_of<N>() * 8);
}

enum { FINE, COARSE, COARSE_REG };
template <int N, int MODE>
__device__ __forceinline__ void chunk(float (&acc)[32], const uint32_t (&W)[96], const uint32_t (&A)[16], uint32_t zero,
                                      const Ctx& cx, uint32_t pu, bool& ready) {
    constexpr int KC = N % 6;
    constexpr int B  = slot_of<N>() * 512;
    if (!ready) mbar_wait(cx.sbase + OFF_FULL + slot_of<N>() * 8, phase_of<N>(pu));
    ready = mbar_try(cx.sbase + OFF_FULL + slot_of<N + 1>() * 8, phase_of<N + 1>(pu));
    if (MODE == FINE) {
        wg_fence();
        wgmma_rs<B + 0>(acc, W[KC * 16 + 0],  W[KC * 16 + 1],  W[KC * 16 + 2],  W[KC * 16 + 3], cx.db0);
        wgmma_rs<B + 2>(acc, W[KC * 16 + 4],  W[KC * 16 + 5],  W[KC * 16 + 6],  W[KC * 16 + 7], cx.db0);
        wgmma_rs<B + 4>(acc, W[KC * 16 + 8],  W[KC * 16 + 9],  W[KC * 16 + 10], W[KC * 16 + 11], cx.db0);
        wgmma_rs<B + 6>(acc, W[KC * 16 + 12], W[KC * 16 + 13], W[KC * 16 + 14], W[KC * 16 + 15], cx.db0);
    } else {
        if (MODE == COARSE) {
            wg_fence();
            wgmma_ss<(KC > 0), KC * 4 * 128, B>(acc, cx.da0, cx.db0);
        } else {
            uint32_t a[4];
#pragma unroll
            for (int i = 0; i < 4; i++) asm volatile("xor.b32 %0, %1, %2;" : "=r"(a[i]) : "r"(A[((KC + 2) & 3) * 4 + i]), "r"(zero));
            wg_fence();
            wgmma_rs<B>(acc, a[0], a[1], a[2], a[3], cx.db0);
            wg_commit();
        }
        wgmma_ss<1, (KC * 4 + 1) * 128, B + 2>(acc, cx.da0, cx.db0);
        wgmma_ss<1, (KC * 4 + 2) * 128, B + 4>(acc, cx.da0, cx.db0);
        wgmma_ss<1, (KC * 4 + 3) * 128, B + 6>(acc, cx.da0, cx.db0);
    }
    wg_commit();
    if (KC > 0) {
        wg_wait<1>();
        release<N - (KC > 0)>(cx);
    }
}

__device__ __forceinline__ int seg_row(int g) {
    const int y = g / 12;
    return y * (2 * HW) + (g - y * 12) * 32;
}

template <int NP>
__global__ void __cluster_dims__(2, 1, 1) __launch_bounds__(NTHREADS, 1)
fpn_kernel(Scratch* scr, const __nv_bfloat16* __restrict__ c_ptr, const __nv_bfloat16* __restrict__ p_ptr,
           const int nsteps, const float one, const uint32_t zero,
           const __grid_constant__ CUtensorMap tm_wo, const __grid_constant__ CUtensorMap tm_wl3,
           const __grid_constant__ CUtensorMap tm_p8, const __grid_constant__ CUtensorMap tm_c,
           const __grid_constant__ CUtensorMap tm_p, const __grid_constant__ CUtensorMap tm_out)
{
    extern __shared__ __align__(1024) uint8_t smem[];
    const uint32_t sbase = smem_u32(smem);
    const int tid   = threadIdx.x;
    const int warp  = __shfl_sync(0xffffffffu, tid >> 5, 0);
    const int lane  = tid & 31;
    const int rank  = blockIdx.x & 1;
    const int pair  = blockIdx.x >> 1;
    const int npair = NP ? NP : gridDim.x >> 1;
    const int nfine = NP ? NSEG / (NP ? NP : 1) : nsteps;

    if (tid == 480) {
        prefetch_tmap(&tm_wo); prefetch_tmap(&tm_wl3); prefetch_tmap(&tm_p8);
        prefetch_tmap(&tm_c); prefetch_tmap(&tm_p); prefetch_tmap(&tm_out);
    }
    if (warp == 12 && elect_one()) {
        for (int s = 0; s < 3; s++) mbar_init(sbase + OFF_FULL + s * 8, 1);
        asm volatile("fence.mbarrier_init.release.cluster;" ::: "memory");
        asm volatile("fence.proxy.async.shared::cta;" ::: "memory");
        const int g0 = pair % 3;
#pragma unroll 1
        for (int s = 0; s < 3; s++) {
            const uint32_t bar = sbase + OFF_FULL + s * 8;
            const uint32_t dst = sbase + OFF_WOUT + g0 * WOUT_SLICE + s * 16384;
            mbar_expect_tx(bar, pair < NJOBS ? 3 * SLOT_BYTES : 2 * SLOT_BYTES);
            tma_load_2d(dst, &tm_wo, rank * 192 + g0 * 64, s * 128, bar);
            if (pair < NJOBS) tma_load_3d(sbase + OFF_RING + s * SLOT_BYTES, &tm_wl3, 0, (pair / 3) * 32, 2 * s, bar);
        }
    }
    if (warp == 13) {
        if (lane == 0) {
            for (int s = 0; s < NSLOTS; s++) {
                if (s >= 3) mbar_init(sbase + OFF_FULL + s * 8, 1);
                mbar_init(sbase + OFF_EMPTY + s * 8, 6);
            }
            mbar_init(sbase + OFF_JB2, 1);
            asm volatile("st.volatile.shared.u32 [%0], %1;" ::"r"(sbase + OFF_PACE), "r"(6) : "memory");
            asm volatile("fence.mbarrier_init.release.cluster;" ::: "memory");
            asm volatile("fence.proxy.async.shared::cta;" ::: "memory");
        }
        __syncwarp();
        asm volatile("bar.arrive 5, 448;" ::: "memory");
    }
    __syncwarp();
    asm volatile("barrier.cluster.arrive.relaxed.aligned;" ::: "memory");

    if (warp >= 12) {
        asm volatile("setmaxnreg.dec.sync.aligned.u32 32;");
        if (warp == 12) {
            asm volatile("bar.sync 5, 448;" ::: "memory");
            if (elect_one()) {
                const int g1 = (pair + 1) % 3, g2 = (pair + 2) % 3;
#pragma unroll 1
                for (int kc = 0; kc < 6; kc++) {
                    const uint32_t bar = sbase + OFF_FULL + (3 + kc) * 8;
                    mbar_expect_tx(bar, (kc & 1) ? SLOT_BYTES : 5 * SLOT_BYTES);
                    tma_load_5d(sbase + OFF_RING + (3 + kc) * SLOT_BYTES, &tm_p8, kc * 64, pair * 2, 0, bar);
                    if (!(kc & 1)) {
                        tma_load_2d(sbase + OFF_WOUT + g1 * WOUT_SLICE + kc * 8192, &tm_wo, rank * 192 + g1 * 64, kc * 64, bar);
                        tma_load_2d(sbase + OFF_WOUT + g2 * WOUT_SLICE + kc * 8192, &tm_wo, rank * 192 + g2 * 64, kc * 64, bar);
                    }
                }
            }
            __syncwarp();
        }
        asm volatile("barrier.cluster.wait.aligned;" ::: "memory");
        if (warp == 12) {
            const uint32_t dst0 = sbase + OFF_RING + rank * 4096;
            uint32_t so = 9 * 8, ph = 1, step = 6;
            auto next_slot = [&]() {
                so += 8;
                if (so == NSLOTS * 8) { so = 0; ph ^= 1; }
            };
            unsigned mytiles = 0, seen = 0;
            auto look = [&]() {
                asm volatile("ld.relaxed.gpu.global.u32 %0, [%1];" : "=r"(seen) : "l"(&scr->prog) : "memory");
            };
            auto tile = [&](bool coarse, int coord, uint64_t pol, bool last) {
                if (rank == 0 && mytiles >= GOV_START) {
                    const unsigned need = mytiles * npair - 2 * max(GOV_TIGHT - (int)mytiles, 0);
                    unsigned spins = 0;
                    while (__any_sync(0xffffffffu, (int)(need - seen) > 0) && ++spins < 100000u) look();
                }
                mytiles++;
#pragma unroll
                for (int kc = 0; kc < 6; kc++) {
                    const uint32_t bar = sbase + OFF_FULL + so, dst = dst0 + so * (SLOT_BYTES / 8);
                    mbar_wait_bounded(sbase + OFF_EMPTY + so, ph);
                    step++;
                    if (elect_one()) {
                        mbar_expect_tx(bar, SLOT_BYTES);
                        if (coarse) tma_load_5d_mc(dst, &tm_p, kc * 64, pair * 2, coord, bar, pol);
                        else        tma_load_2d_mc(dst, &tm_c, kc * 64, coord, bar, pol);
                        asm volatile("st.volatile.shared.u32 [%0], %1;" ::"r"(sbase + OFF_PACE), "r"(step) : "memory");
                    }
                    if (kc == 0 && rank == 0 && lane == 0 && !last)
                        asm volatile("red.relaxed.gpu.global.add.u32 [%0], 1;" ::"l"(&scr->prog) : "memory");
                    next_slot();
                    if (kc == 3 && rank == 0) look();
                }
            };
#pragma unroll 1
            for (int j = 0; j < nfine; j++) {
                const uint64_t pol = j >= nfine - EF_STEPS ? POLICY_EVICT_FIRST : POLICY_EVICT_NORMAL;
                if ((j & 3) == 0 && j > 0) tile(true, j + 2 * rank, pol, false);
                tile(false, seg_row(j * npair + pair) + rank * HW, pol, j + 1 == nfine);
            }
            if (rank == 0 && lane == 0) {
                if (atomicAdd(&scr->prog, 1u) + 1 == mytiles * npair) {
                    asm volatile("st.relaxed.gpu.global.u32 [%0], 0;" ::"l"(&scr->prog) : "memory");
                    asm volatile("red.relaxed.gpu.global.add.u32 [%0], 1;" ::"l"(&scr->epoch) : "memory");
                }
            }
            __syncwarp();
            for (int s = 0; s < NSLOTS; s++) {
                mbar_wait_bounded(sbase + OFF_EMPTY + so, ph);
                next_slot();
            }
        } else if (warp == 13) {
#pragma unroll 1
            for (int i = PF_START; i < nfine + nfine / 4; i++) {
                const int k5 = i / 5, t = i - k5 * 5;
                const char *b0, *b1;
                if (t == 0) {
                    b0 = (const char*)p_ptr + (size_t)((4 * k5 + 2 * rank) * npair + pair) * (16 * C * 2);
                    b1 = b0 + (size_t)npair * (16 * C * 2);
                } else {
                    b0 = (const char*)c_ptr + (size_t)(seg_row((4 * k5 + t - 1) * npair + pair) + rank * HW) * (C * 2);
                    b1 = b0 + 16 * C * 2;
                }
                const int need = max(6 * i - max(PF_LEAD0 - max(i - PF_DECAY, 0), PF_LEAD), PF_FIRST);
                unsigned spins = 0;
                while (true) {
                    uint32_t v;
                    asm volatile("ld.volatile.shared.u32 %0, [%1];" : "=r"(v) : "r"(sbase + OFF_PACE) : "memory");
                    if ((int)v >= need || ++spins > 4000000u) break;
                    __nanosleep(20);
                }
#pragma unroll
                for (int k = 0; k < 6; k++) {
                    asm volatile("prefetch.global.L2 [%0];" ::"l"((k < 3 ? b0 : b1) + lane * 128 + (k % 3) * 4096) : "memory");
                    __nanosleep(i < PF_START + 2 ? PF_GAP0 : PF_GAP);
                }
            }
        } else if (warp == 15) {
            uint32_t par, v;
            asm volatile("ld.relaxed.gpu.global.u32 %0, [%1];" : "=r"(par) : "l"(&scr->epoch) : "memory");
            uint4* clr = scr->wfrag + (~par & 1) * (6 * NFRAG * 128);
            unsigned spins = 0;
            do {
                __nanosleep(500);
                asm volatile("ld.volatile.shared.u32 %0, [%1];" : "=r"(v) : "r"(sbase + OFF_PACE) : "memory");
            } while (v < CLR_AT && ++spins < 100000u);
            for (int i = blockIdx.x * 32 + lane; i < 6 * NFRAG * 128; i += npair * 64) clr[i] = make_uint4(0u, 0u, 0u, 0u);
        }
    } else {
        uint32_t par;
        asm volatile("ld.relaxed.gpu.global.u32 %0, [%1];" : "=r"(par) : "l"(&scr->epoch) : "memory");
        asm volatile("setmaxnreg.inc.sync.aligned.u32 160;");
        asm volatile("bar.sync 5, 448;" ::: "memory");
        const int wg   = warp >> 2;
        const int wtid = tid & 127;
        Ctx cx;
        cx.sbase     = sbase;
        cx.empty_tgt = mapa(sbase + OFF_EMPTY, warp & 1);
        cx.signal    = (lane == 0) && ((warp & 3) < 2);
        cx.db0       = desc_lo(sbase + OFF_RING);
        cx.da0       = desc_lo(sbase + OFF_WOUT + wg * WOUT_SLICE);
        const int cb = rank * 3 + wg;

        float    acc[32];
        uint32_t qp[16];
        uint32_t W[96];

        {
            uint32_t jph = 0;
            for (int job = pair; job < NJOBS; job += npair) {
                if (job % 3 == wg) {
                    if (job != pair) {
                        named_bar(wg);
                        if (wtid == 0) {
                            mbar_expect_tx(sbase + OFF_JB2, 6 * 4096);
                            for (int s = 0; s < 3; s++)
                                tma_load_3d(sbase + OFF_RING + s * SLOT_BYTES, &tm_wl3, 0, (job / 3) * 32, 2 * s, sbase + OFF_JB2);
                        }
                        for (int kc = 0; kc < 6; kc++) mbar_wait(sbase + OFF_FULL + (3 + kc) * 8, 0);
                        mbar_wait(sbase + OFF_JB2, jph);
                    }
                    float ja[16];
#define JOBK(k) wgmma_ss32<((k) > 0), (k) * 128, ((k) >> 2) * 256 + ((k) & 3) * 2>(ja, cx.da0, cx.db0);
                    mbar_wait(sbase + OFF_FULL, 0);
                    wg_fence();
                    JOBK(0)  JOBK(1)  JOBK(2)  JOBK(3)  JOBK(4)  JOBK(5)  JOBK(6)  JOBK(7)
                    wg_commit();
                    mbar_wait(sbase + OFF_FULL + 8, 0);
                    wg_fence();
                    JOBK(8)  JOBK(9)  JOBK(10) JOBK(11) JOBK(12) JOBK(13) JOBK(14) JOBK(15)
                    wg_commit();
                    mbar_wait(sbase + OFF_FULL + 16, 0);
                    wg_fence();
                    JOBK(16) JOBK(17) JOBK(18) JOBK(19) JOBK(20) JOBK(21) JOBK(22) JOBK(23)
#undef JOBK
                    wg_commit();
                    wg_wait<0>();
                    const int fidx = (cb * NFRAG + (job / 3) * 2) * 128 + wtid;
                    uint4* dst = scr->wfrag + (par & 1) * (6 * NFRAG * 128) + fidx;
#pragma unroll
                    for (int i = 0; i < 2; i++) {
                        asm volatile("st.relaxed.gpu.global.v4.u32 [%0], {%1, %2, %3, %4};" ::"l"(dst + i * 128),
                                     "r"(pack_neg(ja[8 * i + 0], ja[8 * i + 1])), "r"(pack_neg(ja[8 * i + 2], ja[8 * i + 3])),
                                     "r"(pack_neg(ja[8 * i + 4], ja[8 * i + 5])), "r"(pack_neg(ja[8 * i + 6], ja[8 * i + 7])) : "memory");
                    }
                }
                if (job + npair < NJOBS) asm volatile("bar.sync 4, 384;" ::: "memory");
                if (job != pair) jph ^= 1;
            }
        }

        par &= 1;
        if (pair < NJOBS) asm volatile("bar.sync 6, 384;" ::: "memory");
        asm volatile("barrier.cluster.wait.aligned;" ::: "memory");

        mbar_wait(sbase + OFF_FULL, 0);
        mbar_wait(sbase + OFF_FULL + 8, 0);
        mbar_wait(sbase + OFF_FULL + 16, 0);
        if (cx.signal) {
            mbar_arrive_cluster(cx.empty_tgt);
            mbar_arrive_cluster(cx.empty_tgt + 8);
            mbar_arrive_cluster(cx.empty_tgt + 16);
        }
        auto pack_q = [&]() {
            uint32_t all = 0;
#pragma unroll
            for (int i = 0; i < 16; i++) {
                qp[i] = pack_bf16(acc[2 * i], acc[2 * i + 1]);
                if (i >= 4) all |= qp[i];
            }
            qp[3] |= all & zero;
        };
        bool ready = false;
        uint32_t pu = 0;
#define CHUNK(N, MODE) chunk<N, MODE>(acc, W, qp, zero, cx, pu, ready)

        const uint4* wsrc = scr->wfrag + (par * 6 + cb) * (NFRAG * 128) + wtid;
        auto load_w = [&](int kc) {
#pragma unroll
            for (int s = 4 * kc; s < 4 * kc + 4; s++) {
                asm volatile("ld.relaxed.gpu.global.v4.u32 {%0, %1, %2, %3}, [%4];"
                             : "=r"(W[4 * s]), "=r"(W[4 * s + 1]), "=r"(W[4 * s + 2]), "=r"(W[4 * s + 3])
                             : "l"(wsrc + s * 128) : "memory");
            }
        };
        auto check_w = [&](int kc) {
            uint32_t* w = kc < 6 ? W + 16 * kc : qp;
            asm volatile(
                "{\n.reg .pred p;\n.reg .u32 m, n;\n"
                "mov.u32 n, 0;\n"
                "CHK_%=:\n"
                "mov.u32 m, %%clock;\n or.b32 m, m, 1;\n min.u32 m, m, %0;\n"
                "min.u32 m, m, %1;\n min.u32 m, m, %2;\n min.u32 m, m, %3;\n min.u32 m, m, %4;\n min.u32 m, m, %5;\n"
                "min.u32 m, m, %6;\n min.u32 m, m, %7;\n min.u32 m, m, %8;\n min.u32 m, m, %9;\n min.u32 m, m, %10;\n"
                "min.u32 m, m, %11;\n min.u32 m, m, %12;\n min.u32 m, m, %13;\n min.u32 m, m, %14;\n min.u32 m, m, %15;\n"
                "setp.ne.u32 p, m, 0;\n"
                "vote.sync.all.pred p, p, 0xffffffff;\n"
                "@p bra.uni OK_%=;\n"
                "add.u32 n, n, 1;\n"
                "setp.gt.u32 p, n, 5000000;\n"
                "@p bra.uni OK_%=;\n"
                "ld.relaxed.gpu.global.v4.u32 {%0, %1, %2, %3}, [%16];\n"
                "ld.relaxed.gpu.global.v4.u32 {%4, %5, %6, %7}, [%16 + 2048];\n"
                "ld.relaxed.gpu.global.v4.u32 {%8, %9, %10, %11}, [%16 + 4096];\n"
                "ld.relaxed.gpu.global.v4.u32 {%12, %13, %14, %15}, [%16 + 6144];\n"
                "bra.uni CHK_%=;\n"
                "OK_%=:\n}"
                : "+r"(w[0]), "+r"(w[1]), "+r"(w[2]), "+r"(w[3]), "+r"(w[4]), "+r"(w[5]), "+r"(w[6]), "+r"(w[7]),
                  "+r"(w[8]), "+r"(w[9]), "+r"(w[10]), "+r"(w[11]), "+r"(w[12]), "+r"(w[13]), "+r"(w[14]), "+r"(w[15])
                : "l"(wsrc + kc * 512) : "memory");
        };
        const uint32_t stage = sbase + OFF_WOUT + wg * WOUT_SLICE + 2 * 8192;
        const uint32_t st_addr = stage + (((lane >> 4) * 8 + (lane & 7)) << 7)
                               + (((((warp & 3) << 1) | ((lane >> 3) & 1)) ^ (lane & 7)) << 4);
        auto publish = [&](int s) {
            if (pair == (NJOBS + s) % npair) {
                uint32_t a[4];
                asm volatile("ldmatrix.sync.aligned.m8n8.x4.trans.shared.b16 {%0, %1, %2, %3}, [%4];"
                             : "=r"(a[0]), "=r"(a[1]), "=r"(a[2]), "=r"(a[3]) : "r"(st_addr + s * 8192) : "memory");
                asm volatile("st.relaxed.gpu.global.v4.u32 [%0], {%1, %2, %3, %4};" ::"l"(wsrc + (24 + s) * 128),
                             "r"(enc_neg(a[0])), "r"(enc_neg(a[1])), "r"(enc_neg(a[2])), "r"(enc_neg(a[3])) : "memory");
            }
        };
        CHUNK(0, COARSE);
        CHUNK(1, COARSE);
        CHUNK(2, COARSE);
        publish(0);
        load_w(0);
        CHUNK(3, COARSE);
        publish(1);
        load_w(1);
        CHUNK(4, COARSE);
        publish(2);
        load_w(2);
        CHUNK(5, COARSE);
        publish(3);
        wg_wait<0>();
        release<5>(cx);
        pack_q();

        auto flush_part = [&](int row, int part) {
            if (part == 0) {
                asm volatile("fence.proxy.async.shared::cta;" ::: "memory");
                named_bar(wg);
            }
            if (wtid == 0) {
                tma_store_2d(&tm_out, cb * 64, row + (part >> 1) * HW + (part & 1) * 16, stage + part * 8192, POLICY_EVICT_FIRST);
                if (part == 3) asm volatile("cp.async.bulk.commit_group;" ::: "memory");
            }
        };
        auto init_acc = [&](int t) {
#pragma unroll
            for (int b = 0; b < 2; b++) {
#pragma unroll
                for (int h = 0; h < 2; h++) {
                    const uint32_t q = qp[t * 4 + b * 2 + h];
                    const float lo = __uint_as_float(q << 16), hi = __uint_as_float(q & 0xffff0000u);
#pragma unroll
                    for (int dy = 0; dy < 2; dy++) {
                        acc[16 * dy + 8 * b + 2 * h]         = dy ? dup(lo, one) : lo;
                        acc[16 * dy + 8 * b + 2 * h + 1]     = dup(lo, one);
                        acc[16 * dy + 8 * b + 4 + 2 * h]     = dy ? dup(hi, one) : hi;
                        acc[16 * dy + 8 * b + 4 + 2 * h + 1] = dup(hi, one);
                    }
                }
            }
        };
        auto stage_tile = [&](int slot) {
            if (wtid == 0) asm volatile("cp.async.bulk.wait_group.read 0;" ::: "memory");
            named_bar(wg);
            wg_wait<0>();
            if (cx.signal) mbar_arrive_cluster(cx.empty_tgt + slot * 8);
#pragma unroll
            for (int i = 0; i < 8; i += 2) {
                stsm_x4_t(st_addr + i * 4096,
                          pack_bf16(acc[4 * i + 0], acc[4 * i + 1]), pack_bf16(acc[4 * i + 2], acc[4 * i + 3]),
                          pack_bf16(acc[4 * i + 4], acc[4 * i + 5]), pack_bf16(acc[4 * i + 6], acc[4 * i + 7]));
            }
        };

        auto load_wo = [&]() {
#pragma unroll
            for (int s = 0; s < 4; s++) {
                asm volatile("ld.global.ca.v4.u32 {%0, %1, %2, %3}, [%4];"
                             : "=r"(qp[4 * s]), "=r"(qp[4 * s + 1]), "=r"(qp[4 * s + 2]), "=r"(qp[4 * s + 3])
                             : "l"(wsrc + (24 + s) * 128) : "memory");
            }
        };

        init_acc(0);
        check_w(0);
        load_w(3);
        load_w(4);
        CHUNK(6, FINE);
        check_w(1);
        CHUNK(7, FINE);
        check_w(2);
        CHUNK(8, FINE);
        check_w(3);
        load_w(5);
        CHUNK(9, FINE);
        check_w(4);
        CHUNK(10, FINE);
        check_w(5);
        CHUNK(11, FINE);

        int seg = pair;
        int prow = seg_row(seg);
        while (true) {
            stage_tile(slot_of<11>());
            init_acc(1);
            CHUNK(12, FINE);
            flush_part(prow, 0);
            CHUNK(13, FINE);
            CHUNK(14, FINE);
            flush_part(prow, 1);
            CHUNK(15, FINE);
            flush_part(prow, 2);
            CHUNK(16, FINE);
            flush_part(prow, 3);
            CHUNK(17, FINE);
            seg += npair;
            prow = seg_row(seg);
            stage_tile(slot_of<17>());
            init_acc(2);
            CHUNK(18, FINE);
            flush_part(prow, 0);
            CHUNK(19, FINE);
            CHUNK(20, FINE);
            flush_part(prow, 1);
            CHUNK(21, FINE);
            flush_part(prow, 2);
            CHUNK(22, FINE);
            flush_part(prow, 3);
            CHUNK(23, FINE);
            seg += npair;
            prow = seg_row(seg);
            stage_tile(slot_of<23>());
            init_acc(3);
            CHUNK(24, FINE);
            flush_part(prow, 0);
            CHUNK(25, FINE);
            load_wo();
            CHUNK(26, FINE);
            flush_part(prow, 1);
            CHUNK(27, FINE);
            flush_part(prow, 2);
            CHUNK(28, FINE);
            flush_part(prow, 3);
            CHUNK(29, FINE);
            seg += npair;
            prow = seg_row(seg);
            if (seg + npair >= NSEG) break;
            stage_tile(slot_of<29>());
            CHUNK(30, COARSE);
            flush_part(prow, 0);
            CHUNK(31, COARSE);
            check_w(6);
            CHUNK(32, COARSE_REG);
            CHUNK(33, COARSE_REG);
            flush_part(prow, 1);
            CHUNK(34, COARSE_REG);
            CHUNK(35, COARSE_REG);
            wg_wait<0>();
            release<35>(cx);
            pack_q();
            init_acc(0);
            CHUNK(36, FINE);
            flush_part(prow, 2);
            CHUNK(37, FINE);
            CHUNK(38, FINE);
            CHUNK(39, FINE);
            flush_part(prow, 3);
            CHUNK(40, FINE);
            CHUNK(41, FINE);
            seg += npair;
            prow = seg_row(seg);
            pu ^= 1;
        }
#undef CHUNK
        stage_tile(slot_of<29>());
#pragma unroll
        for (int part = 0; part < 4; part++) flush_part(prow, part);
        if (wtid == 0) asm volatile("cp.async.bulk.wait_group.read 0;" ::: "memory");
    }
}

typedef CUresult (*EncodeFn)(CUtensorMap*, CUtensorMapDataType, cuuint32_t, void*, const cuuint64_t*, const cuuint64_t*,
                             const cuuint32_t*, const cuuint32_t*, CUtensorMapInterleave, CUtensorMapSwizzle,
                             CUtensorMapL2promotion, CUtensorMapFloatOOBfill);

void encode(EncodeFn fn, CUtensorMap* tm, const void* ptr, int rank, const cuuint64_t* dims, const cuuint64_t* strides,
            const cuuint32_t* box) {
    const cuuint32_t es[5] = {1, 1, 1, 1, 1};
    fn(tm, CU_TENSOR_MAP_DATA_TYPE_BFLOAT16, (cuuint32_t)rank, const_cast<void*>(ptr), dims, strides, box, es,
       CU_TENSOR_MAP_INTERLEAVE_NONE, CU_TENSOR_MAP_SWIZZLE_128B, CU_TENSOR_MAP_L2_PROMOTION_NONE,
       CU_TENSOR_MAP_FLOAT_OOB_FILL_NONE);
}

}

extern "C" void kernel_launch(void* const* d_in, const int* in_sizes, int n_in, void* d_out, int out_size) {
    (void)in_sizes; (void)n_in; (void)out_size;
    const __nv_bfloat16* c_fine   = (const __nv_bfloat16*)d_in[0];
    const __nv_bfloat16* p_coarse = (const __nv_bfloat16*)d_in[1];
    const __nv_bfloat16* w_lat    = (const __nv_bfloat16*)d_in[2];
    const __nv_bfloat16* w_out    = (const __nv_bfloat16*)d_in[3];

    static EncodeFn fn = nullptr;
    static int np = 0;
    static Scratch* scr = nullptr;
    if (!fn) {
        void* p = nullptr;
        cudaDriverEntryPointQueryResult qr;
        cudaGetDriverEntryPoint("cuTensorMapEncodeTiled", &p, cudaEnableDefault, &qr);
        fn = (EncodeFn)p;
        cudaGetSymbolAddress((void**)&scr, g_scratch);
        cudaFuncSetAttribute(fpn_kernel<NPAIRS>, cudaFuncAttributeMaxDynamicSharedMemorySize, SMEM_BYTES);
        cudaFuncSetAttribute(fpn_kernel<0>, cudaFuncAttributeMaxDynamicSharedMemorySize, SMEM_BYTES);
        cudaLaunchConfig_t cfg = {};
        cfg.gridDim = dim3(2); cfg.blockDim = dim3(NTHREADS); cfg.dynamicSmemBytes = SMEM_BYTES;
        cudaLaunchAttribute at[1];
        at[0].id = cudaLaunchAttributeClusterDimension;
        at[0].val.clusterDim.x = 2; at[0].val.clusterDim.y = 1; at[0].val.clusterDim.z = 1;
        cfg.attrs = at; cfg.numAttrs = 1;
        if (cudaOccupancyMaxActiveClusters(&np, fpn_kernel<0>, &cfg) != cudaSuccess || np < 1) np = 1;
        if (np > NPAIRS) np = NPAIRS;
        while ((NSEG / 4) % np) np--;
    }

    CUtensorMap tm_c, tm_p, tm_wl3, tm_out, tm_p8, tm_wo;
    {
        const cuuint64_t dims[2] = {(cuuint64_t)C, (cuuint64_t)NPIX};
        const cuuint64_t str[1]  = {(cuuint64_t)C * 2};
        const cuuint32_t box_in[2]  = {64, 32};
        const cuuint32_t box_out[2] = {64, 16};
        encode(fn, &tm_c, c_fine, 2, dims, str, box_in);
        encode(fn, &tm_out, d_out, 2, dims, str, box_out);
    }
    {
        const cuuint64_t dims[5] = {(cuuint64_t)C, 2, 4, (cuuint64_t)(2 * np), (cuuint64_t)(NSEG / np)};
        const cuuint64_t str[4]  = {(cuuint64_t)4 * C * 2, (cuuint64_t)C * 2, (cuuint64_t)8 * C * 2, (cuuint64_t)np * 16 * C * 2};
        const cuuint32_t box[5]  = {64, 2, 4, 2, 2};
        encode(fn, &tm_p, p_coarse, 5, dims, str, box);
        const cuuint32_t box8[5] = {64, 2, 4, 2, 4};
        encode(fn, &tm_p8, p_coarse, 5, dims, str, box8);
    }
    {
        const cuuint64_t dims[2] = {(cuuint64_t)C, (cuuint64_t)C};
        const cuuint64_t str[1]  = {(cuuint64_t)C * 2};
        const cuuint32_t box[2] = {64, 128};
        encode(fn, &tm_wo, w_out, 2, dims, str, box);
    }
    {
        const cuuint64_t dims[3] = {64, (cuuint64_t)C, 6};
        const cuuint64_t str[2]  = {(cuuint64_t)C * 2, 128};
        const cuuint32_t box[3]  = {64, 32, 2};
        encode(fn, &tm_wl3, w_lat, 3, dims, str, box);
    }
    auto kernel = np == NPAIRS ? fpn_kernel<NPAIRS> : fpn_kernel<0>;
    kernel<<<2 * np, NTHREADS, SMEM_BYTES>>>(scr, c_fine, p_coarse, NSEG / np, 1.0f, 0u,
                                             tm_wo, tm_wl3, tm_p8, tm_c, tm_p, tm_out);
}
```

```cpp
#include <cuda_runtime.h>
#include <cuda_bf16.h>
#include <cuda.h>
#include <stdint.h>

namespace {

constexpr int C          = 384;
constexpr int HW         = 384;
constexpr int NPIX       = HW * HW;
constexpr int NSEG       = NPIX / 64;
constexpr int NJOBS      = 36;

constexpr int NFRAG      = 28;
constexpr int NSLOTS     = 10;
constexpr int NPAIRS     = 64;
constexpr int PF_LEAD    = 5;
constexpr int PF_LEAD0   = 18;
constexpr int PF_DECAY   = 11;
constexpr int PF_FIRST   = 11;
constexpr int PF_GAP     = 50;
constexpr int PF_GAP0    = 150;
constexpr int GOV_START  = 10;
constexpr int GOV_TIGHT  = 24;
constexpr int EF_STEPS   = 10;
constexpr int CLR_AT     = 20;

constexpr int SLOT_BYTES  = 8192;
constexpr int WOUT_SLICE  = 384 * 128;
constexpr int OFF_WOUT    = 0;
constexpr int OFF_RING    = 3 * WOUT_SLICE;
constexpr int OFF_FULL    = OFF_RING + NSLOTS * SLOT_BYTES;
constexpr int OFF_EMPTY   = OFF_FULL + 8 * NSLOTS;
constexpr int OFF_JB2     = OFF_EMPTY + 8 * NSLOTS;
constexpr int OFF_PACE    = OFF_JB2 + 8;
constexpr int OFF_NB      = OFF_PACE + 8;
constexpr int OFF_SINK    = (OFF_NB + 8 + 127) / 128 * 128;
constexpr int SMEM_BYTES  = OFF_SINK + 512;
static_assert(SMEM_BYTES <= 232448, "smem");
static_assert(NSLOTS >= 10, "the first tile (nine ring items) is requested in the prologue");


constexpr int NTHREADS = 512;
constexpr uint64_t POLICY_EVICT_FIRST  = 0x12F0000000000000ull;
constexpr uint64_t POLICY_EVICT_NORMAL = 0x1000000000000000ull;

struct Scratch {
    uint4    wfrag[2 * 6 * NFRAG * 128];
    unsigned epoch;
    unsigned pad0[31];
    unsigned prog;
};
__device__ Scratch g_scratch;

__device__ __forceinline__ uint32_t smem_u32(const void* p) { return (uint32_t)__cvta_generic_to_shared(p); }

__device__ __forceinline__ void mbar_init(uint32_t bar, uint32_t cnt) {
    asm volatile("mbarrier.init.shared::cta.b64 [%0], %1;" ::"r"(bar), "r"(cnt) : "memory");
}
__device__ __forceinline__ void mbar_expect_tx(uint32_t bar, uint32_t bytes) {
    asm volatile("mbarrier.arrive.expect_tx.shared::cta.b64 _, [%0], %1;" ::"r"(bar), "r"(bytes) : "memory");
}
__device__ __forceinline__ void mbar_wait_bounded(uint32_t bar, uint32_t parity) {
    asm volatile(
        "{\n"
        ".reg .pred p;\n"
        ".reg .u32 n;\n"
        "mbarrier.try_wait.parity.shared::cta.b64 p, [%0], %1;\n"
        "@p bra DONE_%=;\n"
        "mov.u32 n, 0;\n"
        "WAIT_%=:\n"
        "mbarrier.try_wait.parity.shared::cta.b64 p, [%0], %1;\n"
        "@p bra DONE_%=;\n"
        "add.u32 n, n, 1;\n"
        "setp.lt.u32 p, n, 4000000;\n"
        "@p bra WAIT_%=;\n"
        "trap;\n"
        "DONE_%=:\n"
        "}\n" ::"r"(bar), "r"(parity) : "memory");
}
__device__ __forceinline__ void mbar_wait(uint32_t bar, uint32_t parity) {
    asm volatile(
        "{\n"
        ".reg .pred p;\n"
        "WAIT_%=:\n"
        "mbarrier.try_wait.parity.shared::cta.b64 p, [%0], %1;\n"
        "@!p bra WAIT_%=;\n"
        "}\n" ::"r"(bar), "r"(parity) : "memory");
}
__device__ __forceinline__ bool mbar_try(uint32_t bar, uint32_t parity) {
    uint32_t r;
    asm volatile("{\n.reg .pred p;\nmbarrier.test_wait.parity.shared::cta.b64 p, [%1], %2;\nselp.u32 %0, 1, 0, p;\n}\n"
                 : "=r"(r) : "r"(bar), "r"(parity) : "memory");
    return r != 0;
}
__device__ __forceinline__ void mbar_arrive_cluster(uint32_t cluster_addr) {
    asm volatile("mbarrier.arrive.shared::cluster.b64 _, [%0];" ::"r"(cluster_addr) : "memory");
}
__device__ __forceinline__ uint32_t mapa(uint32_t addr, uint32_t rank) {
    uint32_t r;
    asm("mapa.shared::cluster.u32 %0, %1, %2;" : "=r"(r) : "r"(addr), "r"(rank));
    return r;
}
__device__ __forceinline__ void named_bar(int wg) {
    asm volatile("bar.sync %0, 128;" ::"r"(wg + 1) : "memory");
}

__device__ __forceinline__ void tma_load_2d(uint32_t dst, const CUtensorMap* tm, int c0, int c1, uint32_t bar) {
    asm volatile("cp.async.bulk.tensor.2d.shared::cluster.global.mbarrier::complete_tx::bytes [%0], [%1, {%2, %3}], [%4];"
                 ::"r"(dst), "l"(tm), "r"(c0), "r"(c1), "r"(bar) : "memory");
}
__device__ __forceinline__ void tma_load_3d(uint32_t dst, const CUtensorMap* tm, int c0, int c1, int c2, uint32_t bar) {
    asm volatile("cp.async.bulk.tensor.3d.shared::cluster.global.mbarrier::complete_tx::bytes [%0], [%1, {%2, %3, %4}], [%5];"
                 ::"r"(dst), "l"(tm), "r"(c0), "r"(c1), "r"(c2), "r"(bar) : "memory");
}
__device__ __forceinline__ void tma_load_5d(uint32_t dst, const CUtensorMap* tm, int c0, int c3, int c4, uint32_t bar) {
    asm volatile("cp.async.bulk.tensor.5d.shared::cluster.global.mbarrier::complete_tx::bytes [%0], [%1, {%2, 0, 0, %3, %4}], [%5];"
                 ::"r"(dst), "l"(tm), "r"(c0), "r"(c3), "r"(c4), "r"(bar) : "memory");
}
__device__ __forceinline__ void tma_load_2d_mc(uint32_t dst, const CUtensorMap* tm, int c0, int c1, uint32_t bar, uint64_t pol) {
    asm volatile("cp.async.bulk.tensor.2d.shared::cluster.global.mbarrier::complete_tx::bytes.multicast::cluster.L2::cache_hint"
                 " [%0], [%1, {%2, %3}], [%4], %5, %6;"
                 ::"r"(dst), "l"(tm), "r"(c0), "r"(c1), "r"(bar), "h"((uint16_t)3), "l"(pol) : "memory");
}
__device__ __forceinline__ void tma_load_5d_mc(uint32_t dst, const CUtensorMap* tm, int c0, int c3, int c4, uint32_t bar, uint64_t pol) {
    asm volatile("cp.async.bulk.tensor.5d.shared::cluster.global.mbarrier::complete_tx::bytes.multicast::cluster.L2::cache_hint"
                 " [%0], [%1, {%2, 0, 0, %3, %4}], [%5], %6, %7;"
                 ::"r"(dst), "l"(tm), "r"(c0), "r"(c3), "r"(c4), "r"(bar), "h"((uint16_t)3), "l"(pol) : "memory");
}
__device__ __forceinline__ void tma_store_2d(const CUtensorMap* tm, int c0, int c1, uint32_t src, uint64_t pol) {
    asm volatile("cp.async.bulk.tensor.2d.global.shared::cta.bulk_group.L2::cache_hint [%0, {%1, %2}], [%3], %4;"
                 ::"l"(tm), "r"(c0), "r"(c1), "r"(src), "l"(pol) : "memory");
}
__device__ __forceinline__ bool elect_one() {
    uint32_t r;
    asm volatile("{\n.reg .pred p;\nelect.sync _|p, 0xffffffff;\nselp.u32 %0, 1, 0, p;\n}" : "=r"(r));
    return r != 0;
}
__device__ __forceinline__ void prefetch_tmap(const CUtensorMap* tm) {
    asm volatile("prefetch.tensormap [%0];" ::"l"(tm) : "memory");
}

__device__ __forceinline__ void wg_fence()  { asm volatile("wgmma.fence.sync.aligned;" ::: "memory"); }
__device__ __forceinline__ void wg_commit() { asm volatile("wgmma.commit_group.sync.aligned;" ::: "memory"); }
template <int N> __device__ __forceinline__ void wg_wait() { asm volatile("wgmma.wait_group.sync.aligned %0;" ::"n"(N) : "memory"); }

#define ACC16(a)                                                                                              \
    "+f"(a[0]), "+f"(a[1]), "+f"(a[2]), "+f"(a[3]), "+f"(a[4]), "+f"(a[5]), "+f"(a[6]), "+f"(a[7]),           \
    "+f"(a[8]), "+f"(a[9]), "+f"(a[10]), "+f"(a[11]), "+f"(a[12]), "+f"(a[13]), "+f"(a[14]), "+f"(a[15])
#define ACC32(a)                                                                                              \
    ACC16(a),                                                                                                 \
    "+f"(a[16]), "+f"(a[17]), "+f"(a[18]), "+f"(a[19]), "+f"(a[20]), "+f"(a[21]), "+f"(a[22]), "+f"(a[23]),   \
    "+f"(a[24]), "+f"(a[25]), "+f"(a[26]), "+f"(a[27]), "+f"(a[28]), "+f"(a[29]), "+f"(a[30]), "+f"(a[31])
#define ACC16_STR "{%0, %1, %2, %3, %4, %5, %6, %7, %8, %9, %10, %11, %12, %13, %14, %15}"
#define ACC32_STR                                                                                             \
    "{%0, %1, %2, %3, %4, %5, %6, %7, %8, %9, %10, %11, %12, %13, %14, %15, "                                 \
    "%16, %17, %18, %19, %20, %21, %22, %23, %24, %25, %26, %27, %28, %29, %30, %31}"

template <int BOFF>
__device__ __forceinline__ void wgmma_rs(float (&d)[32], uint32_t a0, uint32_t a1, uint32_t a2, uint32_t a3, uint32_t db_lo) {
    asm volatile("{\n.reg .b64 db;\n.reg .b32 lo;\n"
                 "add.u32 lo, %36, %37;\nmov.b64 db, {lo, 0x40000040};\n"
                 "wgmma.mma_async.sync.aligned.m64n64k16.f32.bf16.bf16 " ACC32_STR
                 ", {%32, %33, %34, %35}, db, 1, -1, 1, 0;\n}"
                 : ACC32(d) : "r"(a0), "r"(a1), "r"(a2), "r"(a3), "r"(db_lo), "n"(BOFF));
}
template <int ACCUM, int AOFF, int BOFF>
__device__ __forceinline__ void wgmma_ss(float (&d)[32], uint32_t da_lo, uint32_t db_lo) {
    asm volatile("{\n.reg .b64 da, db;\n.reg .b32 lo;\n"
                 "add.u32 lo, %32, %34;\nmov.b64 da, {lo, 0x40000040};\n"
                 "add.u32 lo, %36, %35;\nmov.b64 db, {lo, 0x40000040};\n"
                 "wgmma.mma_async.sync.aligned.m64n64k16.f32.bf16.bf16 " ACC32_STR
                 ", da, db, %33, 1, 1, 1, 0;\n}"
                 : ACC32(d) : "r"(da_lo), "n"(ACCUM), "n"(AOFF), "n"(BOFF), "r"(db_lo));
}
template <int ACCUM, int AOFF, int BOFF>
__device__ __forceinline__ void wgmma_ss32(float (&d)[16], uint32_t da_lo, uint32_t db_lo) {
    asm volatile("{\n.reg .b64 da, db;\n.reg .b32 lo;\n"
                 "add.u32 lo, %16, %18;\nmov.b64 da, {lo, 0x40000040};\n"
                 "add.u32 lo, %20, %19;\nmov.b64 db, {lo, 0x40000040};\n"
                 "wgmma.mma_async.sync.aligned.m64n32k16.f32.bf16.bf16 " ACC16_STR
                 ", da, db, %17, 1, 1, 1, 0;\n}"
                 : ACC16(d) : "r"(da_lo), "n"(ACCUM), "n"(AOFF), "n"(BOFF), "r"(db_lo));
}
__device__ __forceinline__ uint32_t desc_lo(uint32_t addr) { return ((addr & 0x3FFFFu) >> 4) | (1u << 16); }
__device__ __forceinline__ uint32_t pack_bf16(float lo, float hi) {
    uint32_t r;
    asm("cvt.rn.bf16x2.f32 %0, %1, %2;" : "=r"(r) : "f"(hi), "f"(lo));
    return r;
}
__device__ __forceinline__ uint32_t enc_neg(uint32_t pair) {
    const uint32_t v = pair ^ 0x80008000u;
    return v == 0u ? 0x80008000u : v;
}
__device__ __forceinline__ uint32_t pack_neg(float lo, float hi) { return enc_neg(pack_bf16(lo, hi)); }
__device__ __forceinline__ float dup(float x, float one) {
    float r;
    asm volatile("mul.f32 %0, %1, %2;" : "=f"(r) : "f"(x), "f"(one));
    return r;
}
__device__ __forceinline__ void stsm_x4_t(uint32_t addr, uint32_t r0, uint32_t r1, uint32_t r2, uint32_t r3) {
    asm volatile("stmatrix.sync.aligned.m8n8.x4.trans.shared.b16 [%0], {%1, %2, %3, %4};"
                 ::"r"(addr), "r"(r0), "r"(r1), "r"(r2), "r"(r3) : "memory");
}

struct Ctx {
    uint32_t sbase;
    uint32_t db0;
    uint32_t da0;
    uint32_t empty_tgt;
    bool     signal;
};

template <int N> __device__ __forceinline__ constexpr uint32_t slot_of() { return (3 + N) % NSLOTS; }
template <int N> __device__ __forceinline__ uint32_t phase_of(uint32_t pu) { return pu ^ (((3 + N) / NSLOTS) & 1); }
template <int N> __device__ __forceinline__ void release(const Ctx& cx) {
    if (cx.signal) mbar_arrive_cluster(cx.empty_tgt + slot_of<N>() * 8);
}

enum { FINE, COARSE, COARSE_REG };
template <int N, int MODE>
__device__ __forceinline__ void chunk(float (&acc)[32], const uint32_t (&W)[96], const uint32_t (&A)[16], uint32_t zero,
                                      const Ctx& cx, uint32_t pu, bool& ready) {
    constexpr int KC = N % 6;
    constexpr int B  = slot_of<N>() * 512;
    if (!ready) mbar_wait(cx.sbase + OFF_FULL + slot_of<N>() * 8, phase_of<N>(pu));
    ready = mbar_try(cx.sbase + OFF_FULL + slot_of<N + 1>() * 8, phase_of<N + 1>(pu));
    if (MODE == FINE) {
        wg_fence();
        wgmma_rs<B + 0>(acc, W[KC * 16 + 0],  W[KC * 16 + 1],  W[KC * 16 + 2],  W[KC * 16 + 3], cx.db0);
        wgmma_rs<B + 2>(acc, W[KC * 16 + 4],  W[KC * 16 + 5],  W[KC * 16 + 6],  W[KC * 16 + 7], cx.db0);
        wgmma_rs<B + 4>(acc, W[KC * 16 + 8],  W[KC * 16 + 9],  W[KC * 16 + 10], W[KC * 16 + 11], cx.db0);
        wgmma_rs<B + 6>(acc, W[KC * 16 + 12], W[KC * 16 + 13], W[KC * 16 + 14], W[KC * 16 + 15], cx.db0);
    } else {
        if (MODE == COARSE) {
            wg_fence();
            wgmma_ss<(KC > 0), KC * 4 * 128, B>(acc, cx.da0, cx.db0);
        } else {
            uint32_t a[4];
#pragma unroll
            for (int i = 0; i < 4; i++) asm volatile("xor.b32 %0, %1, %2;" : "=r"(a[i]) : "r"(A[((KC + 2) & 3) * 4 + i]), "r"(zero));
            wg_fence();
            wgmma_rs<B>(acc, a[0], a[1], a[2], a[3], cx.db0);
            wg_commit();
        }
        wgmma_ss<1, (KC * 4 + 1) * 128, B + 2>(acc, cx.da0, cx.db0);
        wgmma_ss<1, (KC * 4 + 2) * 128, B + 4>(acc, cx.da0, cx.db0);
        wgmma_ss<1, (KC * 4 + 3) * 128, B + 6>(acc, cx.da0, cx.db0);
    }
    wg_commit();
    if (KC > 0) {
        wg_wait<1>();
        release<N - (KC > 0)>(cx);
    }
}

__device__ __forceinline__ int seg_row(int g) {
    const int y = g / 12;
    return y * (2 * HW) + (g - y * 12) * 32;
}

template <int NP>
__global__ void __cluster_dims__(2, 1, 1) __launch_bounds__(NTHREADS, 1)
fpn_kernel(Scratch* scr, const __nv_bfloat16* __restrict__ c_ptr, const __nv_bfloat16* __restrict__ p_ptr,
           const int nsteps, const float one, const uint32_t zero,
           const __grid_constant__ CUtensorMap tm_wo, const __grid_constant__ CUtensorMap tm_wl3,
           const __grid_constant__ CUtensorMap tm_p8, const __grid_constant__ CUtensorMap tm_c,
           const __grid_constant__ CUtensorMap tm_p, const __grid_constant__ CUtensorMap tm_out,
           const __grid_constant__ CUtensorMap tm_cf)
{
    extern __shared__ __align__(1024) uint8_t smem[];
    const uint32_t sbase = smem_u32(smem);
    const int tid   = threadIdx.x;
    const int warp  = __shfl_sync(0xffffffffu, tid >> 5, 0);
    const int lane  = tid & 31;
    const int rank  = blockIdx.x & 1;
    const int pair  = blockIdx.x >> 1;
    const int npair = NP ? NP : gridDim.x >> 1;
    const int nfine = NP ? NSEG / (NP ? NP : 1) : nsteps;

    if (tid == 480) {
        prefetch_tmap(&tm_wo); prefetch_tmap(&tm_wl3); prefetch_tmap(&tm_p8);
        prefetch_tmap(&tm_c); prefetch_tmap(&tm_p); prefetch_tmap(&tm_out); prefetch_tmap(&tm_cf);
    }
    if (warp == 12 && elect_one()) {
        for (int s = 0; s < 3; s++) mbar_init(sbase + OFF_FULL + s * 8, 1);
        asm volatile("fence.mbarrier_init.release.cluster;" ::: "memory");
        asm volatile("fence.proxy.async.shared::cta;" ::: "memory");
        const int g0 = pair % 3;
#pragma unroll 1
        for (int s = 0; s < 3; s++) {
            const uint32_t bar = sbase + OFF_FULL + s * 8;
            const uint32_t dst = sbase + OFF_WOUT + g0 * WOUT_SLICE + s * 16384;
            mbar_expect_tx(bar, pair < NJOBS ? 3 * SLOT_BYTES : 2 * SLOT_BYTES);
            tma_load_2d(dst, &tm_wo, rank * 192 + g0 * 64, s * 128, bar);
            if (pair < NJOBS) tma_load_3d(sbase + OFF_RING + s * SLOT_BYTES, &tm_wl3, 0, (pair / 3) * 32, 2 * s, bar);
        }
    }
    if (warp == 13) {
        if (lane == 0) {
            for (int s = 0; s < NSLOTS; s++) {
                if (s >= 3) mbar_init(sbase + OFF_FULL + s * 8, 1);
                mbar_init(sbase + OFF_EMPTY + s * 8, 6);
            }
            mbar_init(sbase + OFF_JB2, 1);
            mbar_init(sbase + OFF_NB, 1);
            asm volatile("st.volatile.shared.u32 [%0], %1;" ::"r"(sbase + OFF_PACE), "r"(6) : "memory");
            asm volatile("fence.mbarrier_init.release.cluster;" ::: "memory");
            asm volatile("fence.proxy.async.shared::cta;" ::: "memory");
        }
        __syncwarp();
        asm volatile("bar.arrive 5, 448;" ::: "memory");
    }
    __syncwarp();
    asm volatile("barrier.cluster.arrive.relaxed.aligned;" ::: "memory");

    if (warp >= 12) {
        asm volatile("setmaxnreg.dec.sync.aligned.u32 32;");
        if (warp == 12) {
            asm volatile("bar.sync 5, 448;" ::: "memory");
            if (elect_one()) {
                const int g1 = (pair + 1) % 3, g2 = (pair + 2) % 3;
#pragma unroll 1
                for (int kc = 0; kc < 6; kc++) {
                    const uint32_t bar = sbase + OFF_FULL + (3 + kc) * 8;
                    mbar_expect_tx(bar, (kc & 1) ? SLOT_BYTES : 5 * SLOT_BYTES);
                    tma_load_5d(sbase + OFF_RING + (3 + kc) * SLOT_BYTES, &tm_p8, kc * 64, pair * 2, 0, bar);
                    if (!(kc & 1)) {
                        tma_load_2d(sbase + OFF_WOUT + g1 * WOUT_SLICE + kc * 8192, &tm_wo, rank * 192 + g1 * 64, kc * 64, bar);
                        tma_load_2d(sbase + OFF_WOUT + g2 * WOUT_SLICE + kc * 8192, &tm_wo, rank * 192 + g2 * 64, kc * 64, bar);
                    }
                }
            }
            __syncwarp();
        }
        asm volatile("barrier.cluster.wait.aligned;" ::: "memory");
        if (warp == 12) {
            const uint32_t dst0 = sbase + OFF_RING + rank * 4096;
            uint32_t so = 9 * 8, ph = 1, step = 6;
            auto next_slot = [&]() {
                so += 8;
                if (so == NSLOTS * 8) { so = 0; ph ^= 1; }
            };
            unsigned mytiles = 0, seen = 0;
            auto look = [&]() {
                asm volatile("ld.relaxed.gpu.global.u32 %0, [%1];" : "=r"(seen) : "l"(&scr->prog) : "memory");
            };
            auto tile = [&](bool coarse, int coord, uint64_t pol, bool last) {
                if (rank == 0 && mytiles >= GOV_START) {
                    const unsigned need = mytiles * npair - 2 * max(GOV_TIGHT - (int)mytiles, 0);
                    unsigned spins = 0;
                    while (__any_sync(0xffffffffu, (int)(need - seen) > 0) && ++spins < 100000u) look();
                }
                mytiles++;
#pragma unroll
                for (int kc = 0; kc < 6; kc++) {
                    const uint32_t bar = sbase + OFF_FULL + so, dst = dst0 + so * (SLOT_BYTES / 8);
                    mbar_wait_bounded(sbase + OFF_EMPTY + so, ph);
                    step++;
                    if (elect_one()) {
                        mbar_expect_tx(bar, SLOT_BYTES);
                        if (coarse) tma_load_5d_mc(dst, &tm_p, kc * 64, pair * 2, coord, bar, pol);
                        else        tma_load_2d_mc(dst, &tm_c, kc * 64, coord, bar, pol);
                        asm volatile("st.volatile.shared.u32 [%0], %1;" ::"r"(sbase + OFF_PACE), "r"(step) : "memory");
                    }
                    if (kc == 0 && rank == 0 && lane == 0 && !last)
                        asm volatile("red.relaxed.gpu.global.add.u32 [%0], 1;" ::"l"(&scr->prog) : "memory");
                    next_slot();
                    if (kc == 3 && rank == 0) look();
                }
            };
#pragma unroll 1
            for (int j = 0; j < nfine; j++) {
                const uint64_t pol = j >= nfine - EF_STEPS ? POLICY_EVICT_FIRST : POLICY_EVICT_NORMAL;
                if ((j & 3) == 0 && j > 0) tile(true, j + 2 * rank, pol, false);
                tile(false, seg_row(j * npair + pair) + rank * HW, pol, j + 1 == nfine);
            }
            if (rank == 0 && lane == 0) {
                if (atomicAdd(&scr->prog, 1u) + 1 == mytiles * npair) {
                    asm volatile("st.relaxed.gpu.global.u32 [%0], 0;" ::"l"(&scr->prog) : "memory");
                    asm volatile("red.relaxed.gpu.global.add.u32 [%0], 1;" ::"l"(&scr->epoch) : "memory");
                }
            }
            __syncwarp();
            for (int s = 0; s < NSLOTS; s++) {
                mbar_wait_bounded(sbase + OFF_EMPTY + so, ph);
                next_slot();
            }
        } else if (warp == 13) {
            auto wait_pace = [&](int need) {
                unsigned spins = 0;
                while (true) {
                    uint32_t v;
                    asm volatile("ld.volatile.shared.u32 %0, [%1];" : "=r"(v) : "r"(sbase + OFF_PACE) : "memory");
                    if ((int)v >= need || ++spins > 4000000u) break;
                    __nanosleep(20);
                }
            };
            wait_pace(PF_FIRST);
            if (lane == 0) mbar_expect_tx(sbase + OFF_NB, 12 * 512);
#pragma unroll 1
            for (int k = 0; k < 12; k++) {
                const int j = k < 6 ? 2 : 3;
                if (lane == 0)
                    tma_load_2d(sbase + OFF_SINK, &tm_cf, 0, (seg_row(j * npair + pair) + rank * HW) * 6 + (k - (j - 2) * 6) * 32,
                                sbase + OFF_NB);
                __nanosleep(PF_GAP0);
            }
#pragma unroll 1
            for (int i = 5; i < nfine + nfine / 4; i++) {
                const int k5 = i / 5, t = i - k5 * 5;
                const char *b0, *b1;
                if (t == 0) {
                    b0 = (const char*)p_ptr + (size_t)((4 * k5 + 2 * rank) * npair + pair) * (16 * C * 2);
                    b1 = b0 + (size_t)npair * (16 * C * 2);
                } else {
                    b0 = (const char*)c_ptr + (size_t)(seg_row((4 * k5 + t - 1) * npair + pair) + rank * HW) * (C * 2);
                    b1 = b0 + 16 * C * 2;
                }
                wait_pace(6 * i - max(PF_LEAD0 - max(i - PF_DECAY, 0), PF_LEAD));
#pragma unroll
                for (int k = 0; k < 6; k++) {
                    asm volatile("prefetch.global.L2 [%0];" ::"l"((k < 3 ? b0 : b1) + lane * 128 + (k % 3) * 4096) : "memory");
                    __nanosleep(PF_GAP);
                }
            }
            mbar_wait_bounded(sbase + OFF_NB, 0);
        } else if (warp == 15) {
            uint32_t par, v;
            asm volatile("ld.relaxed.gpu.global.u32 %0, [%1];" : "=r"(par) : "l"(&scr->epoch) : "memory");
            uint4* clr = scr->wfrag + (~par & 1) * (6 * NFRAG * 128);
            unsigned spins = 0;
            do {
                __nanosleep(500);
                asm volatile("ld.volatile.shared.u32 %0, [%1];" : "=r"(v) : "r"(sbase + OFF_PACE) : "memory");
            } while (v < CLR_AT && ++spins < 100000u);
            for (int i = blockIdx.x * 32 + lane; i < 6 * NFRAG * 128; i += npair * 64) clr[i] = make_uint4(0u, 0u, 0u, 0u);
        }
    } else {
        uint32_t par;
        asm volatile("ld.relaxed.gpu.global.u32 %0, [%1];" : "=r"(par) : "l"(&scr->epoch) : "memory");
        asm volatile("setmaxnreg.inc.sync.aligned.u32 160;");
        asm volatile("bar.sync 5, 448;" ::: "memory");
        const int wg   = warp >> 2;
        const int wtid = tid & 127;
        Ctx cx;
        cx.sbase     = sbase;
        cx.empty_tgt = mapa(sbase + OFF_EMPTY, warp & 1);
        cx.signal    = (lane == 0) && ((warp & 3) < 2);
        cx.db0       = desc_lo(sbase + OFF_RING);
        cx.da0       = desc_lo(sbase + OFF_WOUT + wg * WOUT_SLICE);
        const int cb = rank * 3 + wg;

        float    acc[32];
        uint32_t qp[16];
        uint32_t W[96];

        {
            uint32_t jph = 0;
            for (int job = pair; job < NJOBS; job += npair) {
                if (job % 3 == wg) {
                    if (job != pair) {
                        named_bar(wg);
                        if (wtid == 0) {
                            mbar_expect_tx(sbase + OFF_JB2, 6 * 4096);
                            for (int s = 0; s < 3; s++)
                                tma_load_3d(sbase + OFF_RING + s * SLOT_BYTES, &tm_wl3, 0, (job / 3) * 32, 2 * s, sbase + OFF_JB2);
                        }
                        for (int kc = 0; kc < 6; kc++) mbar_wait(sbase + OFF_FULL + (3 + kc) * 8, 0);
                        mbar_wait(sbase + OFF_JB2, jph);
                    }
                    float ja[16];
#define JOBK(k) wgmma_ss32<((k) > 0), (k) * 128, ((k) >> 2) * 256 + ((k) & 3) * 2>(ja, cx.da0, cx.db0);
                    mbar_wait(sbase + OFF_FULL, 0);
                    wg_fence();
                    JOBK(0)  JOBK(1)  JOBK(2)  JOBK(3)  JOBK(4)  JOBK(5)  JOBK(6)  JOBK(7)
                    wg_commit();
                    mbar_wait(sbase + OFF_FULL + 8, 0);
                    wg_fence();
                    JOBK(8)  JOBK(9)  JOBK(10) JOBK(11) JOBK(12) JOBK(13) JOBK(14) JOBK(15)
                    wg_commit();
                    mbar_wait(sbase + OFF_FULL + 16, 0);
                    wg_fence();
                    JOBK(16) JOBK(17) JOBK(18) JOBK(19) JOBK(20) JOBK(21) JOBK(22) JOBK(23)
#undef JOBK
                    wg_commit();
                    wg_wait<0>();
                    const int fidx = (cb * NFRAG + (job / 3) * 2) * 128 + wtid;
                    uint4* dst = scr->wfrag + (par & 1) * (6 * NFRAG * 128) + fidx;
#pragma unroll
                    for (int i = 0; i < 2; i++) {
                        asm volatile("st.relaxed.gpu.global.v4.u32 [%0], {%1, %2, %3, %4};" ::"l"(dst + i * 128),
                                     "r"(pack_neg(ja[8 * i + 0], ja[8 * i + 1])), "r"(pack_neg(ja[8 * i + 2], ja[8 * i + 3])),
                                     "r"(pack_neg(ja[8 * i + 4], ja[8 * i + 5])), "r"(pack_neg(ja[8 * i + 6], ja[8 * i + 7])) : "memory");
                    }
                }
                if (job + npair < NJOBS) asm volatile("bar.sync 4, 384;" ::: "memory");
                if (job != pair) jph ^= 1;
            }
        }

        par &= 1;
        if (pair < NJOBS) asm volatile("bar.sync 6, 384;" ::: "memory");
        asm volatile("barrier.cluster.wait.aligned;" ::: "memory");

        mbar_wait(sbase + OFF_FULL, 0);
        mbar_wait(sbase + OFF_FULL + 8, 0);
        mbar_wait(sbase + OFF_FULL + 16, 0);
        if (cx.signal) {
            mbar_arrive_cluster(cx.empty_tgt);
            mbar_arrive_cluster(cx.empty_tgt + 8);
            mbar_arrive_cluster(cx.empty_tgt + 16);
        }
        auto pack_q = [&]() {
            uint32_t all = 0;
#pragma unroll
            for (int i = 0; i < 16; i++) {
                qp[i] = pack_bf16(acc[2 * i], acc[2 * i + 1]);
                if (i >= 4) all |= qp[i];
            }
            qp[3] |= all & zero;
        };
        bool ready = false;
        uint32_t pu = 0;
#define CHUNK(N, MODE) chunk<N, MODE>(acc, W, qp, zero, cx, pu, ready)

        const uint4* wsrc = scr->wfrag + (par * 6 + cb) * (NFRAG * 128) + wtid;
        auto load_w = [&](int kc) {
#pragma unroll
            for (int s = 4 * kc; s < 4 * kc + 4; s++) {
                asm volatile("ld.relaxed.gpu.global.v4.u32 {%0, %1, %2, %3}, [%4];"
                             : "=r"(W[4 * s]), "=r"(W[4 * s + 1]), "=r"(W[4 * s + 2]), "=r"(W[4 * s + 3])
                             : "l"(wsrc + s * 128) : "memory");
            }
        };
        auto check_w = [&](int kc) {
            uint32_t* w = kc < 6 ? W + 16 * kc : qp;
            asm volatile(
                "{\n.reg .pred p;\n.reg .u32 m, n;\n"
                "mov.u32 n, 0;\n"
                "CHK_%=:\n"
                "mov.u32 m, %%clock;\n or.b32 m, m, 1;\n min.u32 m, m, %0;\n"
                "min.u32 m, m, %1;\n min.u32 m, m, %2;\n min.u32 m, m, %3;\n min.u32 m, m, %4;\n min.u32 m, m, %5;\n"
                "min.u32 m, m, %6;\n min.u32 m, m, %7;\n min.u32 m, m, %8;\n min.u32 m, m, %9;\n min.u32 m, m, %10;\n"
                "min.u32 m, m, %11;\n min.u32 m, m, %12;\n min.u32 m, m, %13;\n min.u32 m, m, %14;\n min.u32 m, m, %15;\n"
                "setp.ne.u32 p, m, 0;\n"
                "vote.sync.all.pred p, p, 0xffffffff;\n"
                "@p bra.uni OK_%=;\n"
                "add.u32 n, n, 1;\n"
                "setp.gt.u32 p, n, 5000000;\n"
                "@p bra.uni OK_%=;\n"
                "ld.relaxed.gpu.global.v4.u32 {%0, %1, %2, %3}, [%16];\n"
                "ld.relaxed.gpu.global.v4.u32 {%4, %5, %6, %7}, [%16 + 2048];\n"
                "ld.relaxed.gpu.global.v4.u32 {%8, %9, %10, %11}, [%16 + 4096];\n"
                "ld.relaxed.gpu.global.v4.u32 {%12, %13, %14, %15}, [%16 + 6144];\n"
                "bra.uni CHK_%=;\n"
                "OK_%=:\n}"
                : "+r"(w[0]), "+r"(w[1]), "+r"(w[2]), "+r"(w[3]), "+r"(w[4]), "+r"(w[5]), "+r"(w[6]), "+r"(w[7]),
                  "+r"(w[8]), "+r"(w[9]), "+r"(w[10]), "+r"(w[11]), "+r"(w[12]), "+r"(w[13]), "+r"(w[14]), "+r"(w[15])
                : "l"(wsrc + kc * 512) : "memory");
        };
        const uint32_t stage = sbase + OFF_WOUT + wg * WOUT_SLICE + 2 * 8192;
        const uint32_t st_addr = stage + (((lane >> 4) * 8 + (lane & 7)) << 7)
                               + (((((warp & 3) << 1) | ((lane >> 3) & 1)) ^ (lane & 7)) << 4);
        auto publish = [&](int s) {
            if (pair == (NJOBS + s) % npair) {
                uint32_t a[4];
                asm volatile("ldmatrix.sync.aligned.m8n8.x4.trans.shared.b16 {%0, %1, %2, %3}, [%4];"
                             : "=r"(a[0]), "=r"(a[1]), "=r"(a[2]), "=r"(a[3]) : "r"(st_addr + s * 8192) : "memory");
                asm volatile("st.relaxed.gpu.global.v4.u32 [%0], {%1, %2, %3, %4};" ::"l"(wsrc + (24 + s) * 128),
                             "r"(enc_neg(a[0])), "r"(enc_neg(a[1])), "r"(enc_neg(a[2])), "r"(enc_neg(a[3])) : "memory");
            }
        };
        CHUNK(0, COARSE);
        CHUNK(1, COARSE);
        CHUNK(2, COARSE);
        publish(0);
        load_w(0);
        CHUNK(3, COARSE);
        publish(1);
        load_w(1);
        CHUNK(4, COARSE);
        publish(2);
        load_w(2);
        CHUNK(5, COARSE);
        publish(3);
        wg_wait<0>();
        release<5>(cx);
        pack_q();

        auto flush_part = [&](int row, int part) {
            if (part == 0) {
                asm volatile("fence.proxy.async.shared::cta;" ::: "memory");
                named_bar(wg);
            }
            if (wtid == 0) {
                tma_store_2d(&tm_out, cb * 64, row + (part >> 1) * HW + (part & 1) * 16, stage + part * 8192, POLICY_EVICT_FIRST);
                if (part == 3) asm volatile("cp.async.bulk.commit_group;" ::: "memory");
            }
        };
        auto init_acc = [&](int t) {
#pragma unroll
            for (int b = 0; b < 2; b++) {
#pragma unroll
                for (int h = 0; h < 2; h++) {
                    const uint32_t q = qp[t * 4 + b * 2 + h];
                    const float lo = __uint_as_float(q << 16), hi = __uint_as_float(q & 0xffff0000u);
#pragma unroll
                    for (int dy = 0; dy < 2; dy++) {
                        acc[16 * dy + 8 * b + 2 * h]         = dy ? dup(lo, one) : lo;
                        acc[16 * dy + 8 * b + 2 * h + 1]     = dup(lo, one);
                        acc[16 * dy + 8 * b + 4 + 2 * h]     = dy ? dup(hi, one) : hi;
                        acc[16 * dy + 8 * b + 4 + 2 * h + 1] = dup(hi, one);
                    }
                }
            }
        };
        auto stage_tile = [&](int slot) {
            if (wtid == 0) asm volatile("cp.async.bulk.wait_group.read 0;" ::: "memory");
            named_bar(wg);
            wg_wait<0>();
            if (cx.signal) mbar_arrive_cluster(cx.empty_tgt + slot * 8);
#pragma unroll
            for (int i = 0; i < 8; i += 2) {
                stsm_x4_t(st_addr + i * 4096,
                          pack_bf16(acc[4 * i + 0], acc[4 * i + 1]), pack_bf16(acc[4 * i + 2], acc[4 * i + 3]),
                          pack_bf16(acc[4 * i + 4], acc[4 * i + 5]), pack_bf16(acc[4 * i + 6], acc[4 * i + 7]));
            }
        };

        auto load_wo = [&]() {
#pragma unroll
            for (int s = 0; s < 4; s++) {
                asm volatile("ld.global.ca.v4.u32 {%0, %1, %2, %3}, [%4];"
                             : "=r"(qp[4 * s]), "=r"(qp[4 * s + 1]), "=r"(qp[4 * s + 2]), "=r"(qp[4 * s + 3])
                             : "l"(wsrc + (24 + s) * 128) : "memory");
            }
        };

        init_acc(0);
        check_w(0);
        load_w(3);
        load_w(4);
        CHUNK(6, FINE);
        check_w(1);
        CHUNK(7, FINE);
        check_w(2);
        CHUNK(8, FINE);
        check_w(3);
        load_w(5);
        CHUNK(9, FINE);
        check_w(4);
        CHUNK(10, FINE);
        check_w(5);
        CHUNK(11, FINE);

        int seg = pair;
        int prow = seg_row(seg);
        while (true) {
            stage_tile(slot_of<11>());
            init_acc(1);
            CHUNK(12, FINE);
            flush_part(prow, 0);
            CHUNK(13, FINE);
            CHUNK(14, FINE);
            flush_part(prow, 1);
            CHUNK(15, FINE);
            flush_part(prow, 2);
            CHUNK(16, FINE);
            flush_part(prow, 3);
            CHUNK(17, FINE);
            seg += npair;
            prow = seg_row(seg);
            stage_tile(slot_of<17>());
            init_acc(2);
            CHUNK(18, FINE);
            flush_part(prow, 0);
            CHUNK(19, FINE);
            CHUNK(20, FINE);
            flush_part(prow, 1);
            CHUNK(21, FINE);
            flush_part(prow, 2);
            CHUNK(22, FINE);
            flush_part(prow, 3);
            CHUNK(23, FINE);
            seg += npair;
            prow = seg_row(seg);
            stage_tile(slot_of<23>());
            init_acc(3);
            CHUNK(24, FINE);
            flush_part(prow, 0);
            CHUNK(25, FINE);
            load_wo();
            CHUNK(26, FINE);
            flush_part(prow, 1);
            CHUNK(27, FINE);
            flush_part(prow, 2);
            CHUNK(28, FINE);
            flush_part(prow, 3);
            CHUNK(29, FINE);
            seg += npair;
            prow = seg_row(seg);
            if (seg + npair >= NSEG) break;
            stage_tile(slot_of<29>());
            CHUNK(30, COARSE);
            flush_part(prow, 0);
            CHUNK(31, COARSE);
            check_w(6);
            CHUNK(32, COARSE_REG);
            CHUNK(33, COARSE_REG);
            flush_part(prow, 1);
            CHUNK(34, COARSE_REG);
            CHUNK(35, COARSE_REG);
            wg_wait<0>();
            release<35>(cx);
            pack_q();
            init_acc(0);
            CHUNK(36, FINE);
            flush_part(prow, 2);
            CHUNK(37, FINE);
            CHUNK(38, FINE);
            CHUNK(39, FINE);
            flush_part(prow, 3);
            CHUNK(40, FINE);
            CHUNK(41, FINE);
            seg += npair;
            prow = seg_row(seg);
            pu ^= 1;
        }
#undef CHUNK
        stage_tile(slot_of<29>());
#pragma unroll
        for (int part = 0; part < 4; part++) flush_part(prow, part);
        if (wtid == 0) asm volatile("cp.async.bulk.wait_group.read 0;" ::: "memory");
    }
}

typedef CUresult (*EncodeFn)(CUtensorMap*, CUtensorMapDataType, cuuint32_t, void*, const cuuint64_t*, const cuuint64_t*,
                             const cuuint32_t*, const cuuint32_t*, CUtensorMapInterleave, CUtensorMapSwizzle,
                             CUtensorMapL2promotion, CUtensorMapFloatOOBfill);

void encode(EncodeFn fn, CUtensorMap* tm, const void* ptr, int rank, const cuuint64_t* dims, const cuuint64_t* strides,
            const cuuint32_t* box, CUtensorMapSwizzle swizzle = CU_TENSOR_MAP_SWIZZLE_128B,
            CUtensorMapL2promotion promotion = CU_TENSOR_MAP_L2_PROMOTION_NONE) {
    const cuuint32_t es[5] = {1, 1, 1, 1, 1};
    fn(tm, CU_TENSOR_MAP_DATA_TYPE_BFLOAT16, (cuuint32_t)rank, const_cast<void*>(ptr), dims, strides, box, es,
       CU_TENSOR_MAP_INTERLEAVE_NONE, swizzle, promotion, CU_TENSOR_MAP_FLOAT_OOB_FILL_NONE);
}

}

extern "C" void kernel_launch(void* const* d_in, const int* in_sizes, int n_in, void* d_out, int out_size) {
    (void)in_sizes; (void)n_in; (void)out_size;
    const __nv_bfloat16* c_fine   = (const __nv_bfloat16*)d_in[0];
    const __nv_bfloat16* p_coarse = (const __nv_bfloat16*)d_in[1];
    const __nv_bfloat16* w_lat    = (const __nv_bfloat16*)d_in[2];
    const __nv_bfloat16* w_out    = (const __nv_bfloat16*)d_in[3];

    static EncodeFn fn = nullptr;
    static int np = 0;
    static Scratch* scr = nullptr;
    if (!fn) {
        void* p = nullptr;
        cudaDriverEntryPointQueryResult qr;
        cudaGetDriverEntryPoint("cuTensorMapEncodeTiled", &p, cudaEnableDefault, &qr);
        fn = (EncodeFn)p;
        cudaGetSymbolAddress((void**)&scr, g_scratch);
        cudaFuncSetAttribute(fpn_kernel<NPAIRS>, cudaFuncAttributeMaxDynamicSharedMemorySize, SMEM_BYTES);
        cudaFuncSetAttribute(fpn_kernel<0>, cudaFuncAttributeMaxDynamicSharedMemorySize, SMEM_BYTES);
        cudaLaunchConfig_t cfg = {};
        cfg.gridDim = dim3(2); cfg.blockDim = dim3(NTHREADS); cfg.dynamicSmemBytes = SMEM_BYTES;
        cudaLaunchAttribute at[1];
        at[0].id = cudaLaunchAttributeClusterDimension;
        at[0].val.clusterDim.x = 2; at[0].val.clusterDim.y = 1; at[0].val.clusterDim.z = 1;
        cfg.attrs = at; cfg.numAttrs = 1;
        if (cudaOccupancyMaxActiveClusters(&np, fpn_kernel<0>, &cfg) != cudaSuccess || np < 1) np = 1;
        if (np > NPAIRS) np = NPAIRS;
        while ((NSEG / 4) % np) np--;
    }

    CUtensorMap tm_cf, tm_c, tm_p, tm_wl3, tm_out, tm_p8, tm_wo;
    {
        const cuuint64_t dims[2] = {(cuuint64_t)C, (cuuint64_t)NPIX};
        const cuuint64_t str[1]  = {(cuuint64_t)C * 2};
        const cuuint32_t box_in[2]  = {64, 32};
        const cuuint32_t box_out[2] = {64, 16};
        encode(fn, &tm_c, c_fine, 2, dims, str, box_in);
        encode(fn, &tm_out, d_out, 2, dims, str, box_out);
    }
    {
        const cuuint64_t dims[5] = {(cuuint64_t)C, 2, 4, (cuuint64_t)(2 * np), (cuuint64_t)(NSEG / np)};
        const cuuint64_t str[4]  = {(cuuint64_t)4 * C * 2, (cuuint64_t)C * 2, (cuuint64_t)8 * C * 2, (cuuint64_t)np * 16 * C * 2};
        const cuuint32_t box[5]  = {64, 2, 4, 2, 2};
        encode(fn, &tm_p, p_coarse, 5, dims, str, box);
        const cuuint32_t box8[5] = {64, 2, 4, 2, 4};
        encode(fn, &tm_p8, p_coarse, 5, dims, str, box8);
    }
    {
        const cuuint64_t dims[2] = {(cuuint64_t)C, (cuuint64_t)C};
        const cuuint64_t str[1]  = {(cuuint64_t)C * 2};
        const cuuint32_t box[2] = {64, 128};
        encode(fn, &tm_wo, w_out, 2, dims, str, box);
    }
    {
        const cuuint64_t dims[3] = {64, (cuuint64_t)C, 6};
        const cuuint64_t str[2]  = {(cuuint64_t)C * 2, 128};
        const cuuint32_t box[3]  = {64, 32, 2};
        encode(fn, &tm_wl3, w_lat, 3, dims, str, box);
    }
    {
        const cuuint64_t dims[2] = {64, (cuuint64_t)NPIX * 6};
        const cuuint64_t str[1]  = {128};
        const cuuint32_t box[2]  = {8, 32};
        encode(fn, &tm_cf, c_fine, 2, dims, str, box, CU_TENSOR_MAP_SWIZZLE_NONE, CU_TENSOR_MAP_L2_PROMOTION_L2_128B);
    }
    auto kernel = np == NPAIRS ? fpn_kernel<NPAIRS> : fpn_kernel<0>;
    kernel<<<2 * np, NTHREADS, SMEM_BYTES>>>(scr, c_fine, p_coarse, NSEG / np, 1.0f, 0u,
                                             tm_wo, tm_wl3, tm_p8, tm_c, tm_p, tm_out, tm_cf);
}
```

```cpp
#include <cuda_runtime.h>
#include <cuda_bf16.h>
#include <cuda.h>
#include <stdint.h>

namespace {

constexpr int C          = 384;
constexpr int HW         = 384;
constexpr int NPIX       = HW * HW;
constexpr int NSEG       = NPIX / 64;
constexpr int NJOBS      = 36;

constexpr int NFRAG      = 28;
constexpr int NSLOTS     = 10;
constexpr int NPAIRS     = 64;
constexpr int PF_LEAD    = 5;
constexpr int PF_LEAD0   = 18;
constexpr int PF_DECAY   = 12;
constexpr int PF_FIRST   = 11;
constexpr int PF_GAP     = 50;
constexpr int GOV_START  = 10;
constexpr int GOV_TIGHT  = 24;
constexpr int EF_STEPS   = 10;
constexpr int CLR_AT     = 20;

constexpr int SLOT_BYTES  = 8192;
constexpr int WOUT_SLICE  = 384 * 128;
constexpr int OFF_WOUT    = 0;
constexpr int OFF_RING    = 3 * WOUT_SLICE;
constexpr int OFF_FULL    = OFF_RING + NSLOTS * SLOT_BYTES;
constexpr int OFF_EMPTY   = OFF_FULL + 8 * NSLOTS;
constexpr int OFF_JB2     = OFF_EMPTY + 8 * NSLOTS;
constexpr int OFF_PACE    = OFF_JB2 + 8;
constexpr int OFF_NB      = OFF_PACE + 8;
constexpr int OFF_SINK    = (OFF_NB + 8 + 127) / 128 * 128;
constexpr int SMEM_BYTES  = OFF_SINK + 512;
static_assert(SMEM_BYTES <= 232448, "smem");
static_assert(NSLOTS >= 10, "the first tile (nine ring items) is requested in the prologue");


constexpr int NTHREADS = 512;
constexpr uint64_t POLICY_EVICT_FIRST  = 0x12F0000000000000ull;
constexpr uint64_t POLICY_EVICT_NORMAL = 0x1000000000000000ull;

struct Scratch {
    uint4    wfrag[2 * 6 * NFRAG * 128];
    unsigned epoch;
    unsigned pad0[31];
    unsigned prog;
};
__device__ Scratch g_scratch;

__device__ __forceinline__ uint32_t smem_u32(const void* p) { return (uint32_t)__cvta_generic_to_shared(p); }

__device__ __forceinline__ void mbar_init(uint32_t bar, uint32_t cnt) {
    asm volatile("mbarrier.init.shared::cta.b64 [%0], %1;" ::"r"(bar), "r"(cnt) : "memory");
}
__device__ __forceinline__ void mbar_expect_tx(uint32_t bar, uint32_t bytes) {
    asm volatile("mbarrier.arrive.expect_tx.shared::cta.b64 _, [%0], %1;" ::"r"(bar), "r"(bytes) : "memory");
}
__device__ __forceinline__ void mbar_wait_bounded(uint32_t bar, uint32_t parity) {
    asm volatile(
        "{\n"
        ".reg .pred p;\n"
        ".reg .u32 n;\n"
        "mbarrier.try_wait.parity.shared::cta.b64 p, [%0], %1;\n"
        "@p bra DONE_%=;\n"
        "mov.u32 n, 0;\n"
        "WAIT_%=:\n"
        "mbarrier.try_wait.parity.shared::cta.b64 p, [%0], %1;\n"
        "@p bra DONE_%=;\n"
        "add.u32 n, n, 1;\n"
        "setp.lt.u32 p, n, 4000000;\n"
        "@p bra WAIT_%=;\n"
        "trap;\n"
        "DONE_%=:\n"
        "}\n" ::"r"(bar), "r"(parity) : "memory");
}
__device__ __forceinline__ void mbar_wait(uint32_t bar, uint32_t parity) {
    asm volatile(
        "{\n"
        ".reg .pred p;\n"
        "WAIT_%=:\n"
        "mbarrier.try_wait.parity.shared::cta.b64 p, [%0], %1;\n"
        "@!p bra WAIT_%=;\n"
        "}\n" ::"r"(bar), "r"(parity) : "memory");
}
__device__ __forceinline__ bool mbar_try(uint32_t bar, uint32_t parity) {
    uint32_t r;
    asm volatile("{\n.reg .pred p;\nmbarrier.test_wait.parity.shared::cta.b64 p, [%1], %2;\nselp.u32 %0, 1, 0, p;\n}\n"
                 : "=r"(r) : "r"(bar), "r"(parity) : "memory");
    return r != 0;
}
__device__ __forceinline__ void mbar_arrive_cluster(uint32_t cluster_addr) {
    asm volatile("mbarrier.arrive.shared::cluster.b64 _, [%0];" ::"r"(cluster_addr) : "memory");
}
__device__ __forceinline__ uint32_t mapa(uint32_t addr, uint32_t rank) {
    uint32_t r;
    asm("mapa.shared::cluster.u32 %0, %1, %2;" : "=r"(r) : "r"(addr), "r"(rank));
    return r;
}
__device__ __forceinline__ void named_bar(int wg) {
    asm volatile("bar.sync %0, 128;" ::"r"(wg + 1) : "memory");
}

__device__ __forceinline__ void tma_load_2d(uint32_t dst, const CUtensorMap* tm, int c0, int c1, uint32_t bar) {
    asm volatile("cp.async.bulk.tensor.2d.shared::cluster.global.mbarrier::complete_tx::bytes [%0], [%1, {%2, %3}], [%4];"
                 ::"r"(dst), "l"(tm), "r"(c0), "r"(c1), "r"(bar) : "memory");
}
__device__ __forceinline__ void tma_load_3d(uint32_t dst, const CUtensorMap* tm, int c0, int c1, int c2, uint32_t bar) {
    asm volatile("cp.async.bulk.tensor.3d.shared::cluster.global.mbarrier::complete_tx::bytes [%0], [%1, {%2, %3, %4}], [%5];"
                 ::"r"(dst), "l"(tm), "r"(c0), "r"(c1), "r"(c2), "r"(bar) : "memory");
}
__device__ __forceinline__ void tma_load_5d(uint32_t dst, const CUtensorMap* tm, int c0, int c3, int c4, uint32_t bar) {
    asm volatile("cp.async.bulk.tensor.5d.shared::cluster.global.mbarrier::complete_tx::bytes [%0], [%1, {%2, 0, 0, %3, %4}], [%5];"
                 ::"r"(dst), "l"(tm), "r"(c0), "r"(c3), "r"(c4), "r"(bar) : "memory");
}
__device__ __forceinline__ void tma_load_2d_mc(uint32_t dst, const CUtensorMap* tm, int c0, int c1, uint32_t bar, uint64_t pol) {
    asm volatile("cp.async.bulk.tensor.2d.shared::cluster.global.mbarrier::complete_tx::bytes.multicast::cluster.L2::cache_hint"
                 " [%0], [%1, {%2, %3}], [%4], %5, %6;"
                 ::"r"(dst), "l"(tm), "r"(c0), "r"(c1), "r"(bar), "h"((uint16_t)3), "l"(pol) : "memory");
}
__device__ __forceinline__ void tma_load_5d_mc(uint32_t dst, const CUtensorMap* tm, int c0, int c3, int c4, uint32_t bar, uint64_t pol) {
    asm volatile("cp.async.bulk.tensor.5d.shared::cluster.global.mbarrier::complete_tx::bytes.multicast::cluster.L2::cache_hint"
                 " [%0], [%1, {%2, 0, 0, %3, %4}], [%5], %6, %7;"
                 ::"r"(dst), "l"(tm), "r"(c0), "r"(c3), "r"(c4), "r"(bar), "h"((uint16_t)3), "l"(pol) : "memory");
}
__device__ __forceinline__ void tma_store_2d(const CUtensorMap* tm, int c0, int c1, uint32_t src, uint64_t pol) {
    asm volatile("cp.async.bulk.tensor.2d.global.shared::cta.bulk_group.L2::cache_hint [%0, {%1, %2}], [%3], %4;"
                 ::"l"(tm), "r"(c0), "r"(c1), "r"(src), "l"(pol) : "memory");
}
__device__ __forceinline__ bool elect_one() {
    uint32_t r;
    asm volatile("{\n.reg .pred p;\nelect.sync _|p, 0xffffffff;\nselp.u32 %0, 1, 0, p;\n}" : "=r"(r));
    return r != 0;
}
__device__ __forceinline__ void prefetch_tmap(const CUtensorMap* tm) {
    asm volatile("prefetch.tensormap [%0];" ::"l"(tm) : "memory");
}

__device__ __forceinline__ void wg_fence()  { asm volatile("wgmma.fence.sync.aligned;" ::: "memory"); }
__device__ __forceinline__ void wg_commit() { asm volatile("wgmma.commit_group.sync.aligned;" ::: "memory"); }
template <int N> __device__ __forceinline__ void wg_wait() { asm volatile("wgmma.wait_group.sync.aligned %0;" ::"n"(N) : "memory"); }

#define ACC16(a)                                                                                              \
    "+f"(a[0]), "+f"(a[1]), "+f"(a[2]), "+f"(a[3]), "+f"(a[4]), "+f"(a[5]), "+f"(a[6]), "+f"(a[7]),           \
    "+f"(a[8]), "+f"(a[9]), "+f"(a[10]), "+f"(a[11]), "+f"(a[12]), "+f"(a[13]), "+f"(a[14]), "+f"(a[15])
#define ACC32(a)                                                                                              \
    ACC16(a),                                                                                                 \
    "+f"(a[16]), "+f"(a[17]), "+f"(a[18]), "+f"(a[19]), "+f"(a[20]), "+f"(a[21]), "+f"(a[22]), "+f"(a[23]),   \
    "+f"(a[24]), "+f"(a[25]), "+f"(a[26]), "+f"(a[27]), "+f"(a[28]), "+f"(a[29]), "+f"(a[30]), "+f"(a[31])
#define ACC16_STR "{%0, %1, %2, %3, %4, %5, %6, %7, %8, %9, %10, %11, %12, %13, %14, %15}"
#define ACC32_STR                                                                                             \
    "{%0, %1, %2, %3, %4, %5, %6, %7, %8, %9, %10, %11, %12, %13, %14, %15, "                                 \
    "%16, %17, %18, %19, %20, %21, %22, %23, %24, %25, %26, %27, %28, %29, %30, %31}"

template <int BOFF>
__device__ __forceinline__ void wgmma_rs(float (&d)[32], uint32_t a0, uint32_t a1, uint32_t a2, uint32_t a3, uint32_t db_lo) {
    asm volatile("{\n.reg .b64 db;\n.reg .b32 lo;\n"
                 "add.u32 lo, %36, %37;\nmov.b64 db, {lo, 0x40000040};\n"
                 "wgmma.mma_async.sync.aligned.m64n64k16.f32.bf16.bf16 " ACC32_STR
                 ", {%32, %33, %34, %35}, db, 1, -1, 1, 0;\n}"
                 : ACC32(d) : "r"(a0), "r"(a1), "r"(a2), "r"(a3), "r"(db_lo), "n"(BOFF));
}
template <int ACCUM, int AOFF, int BOFF>
__device__ __forceinline__ void wgmma_ss(float (&d)[32], uint32_t da_lo, uint32_t db_lo) {
    asm volatile("{\n.reg .b64 da, db;\n.reg .b32 lo;\n"
                 "add.u32 lo, %32, %34;\nmov.b64 da, {lo, 0x40000040};\n"
                 "add.u32 lo, %36, %35;\nmov.b64 db, {lo, 0x40000040};\n"
                 "wgmma.mma_async.sync.aligned.m64n64k16.f32.bf16.bf16 " ACC32_STR
                 ", da, db, %33, 1, 1, 1, 0;\n}"
                 : ACC32(d) : "r"(da_lo), "n"(ACCUM), "n"(AOFF), "n"(BOFF), "r"(db_lo));
}
template <int ACCUM, int AOFF, int BOFF>
__device__ __forceinline__ void wgmma_ss32(float (&d)[16], uint32_t da_lo, uint32_t db_lo) {
    asm volatile("{\n.reg .b64 da, db;\n.reg .b32 lo;\n"
                 "add.u32 lo, %16, %18;\nmov.b64 da, {lo, 0x40000040};\n"
                 "add.u32 lo, %20, %19;\nmov.b64 db, {lo, 0x40000040};\n"
                 "wgmma.mma_async.sync.aligned.m64n32k16.f32.bf16.bf16 " ACC16_STR
                 ", da, db, %17, 1, 1, 1, 0;\n}"
                 : ACC16(d) : "r"(da_lo), "n"(ACCUM), "n"(AOFF), "n"(BOFF), "r"(db_lo));
}
__device__ __forceinline__ uint32_t desc_lo(uint32_t addr) { return ((addr & 0x3FFFFu) >> 4) | (1u << 16); }
__device__ __forceinline__ uint32_t pack_bf16(float lo, float hi) {
    uint32_t r;
    asm("cvt.rn.bf16x2.f32 %0, %1, %2;" : "=r"(r) : "f"(hi), "f"(lo));
    return r;
}
__device__ __forceinline__ uint32_t enc_neg(uint32_t pair) {
    const uint32_t v = pair ^ 0x80008000u;
    return v == 0u ? 0x80008000u : v;
}
__device__ __forceinline__ uint32_t pack_neg(float lo, float hi) { return enc_neg(pack_bf16(lo, hi)); }
__device__ __forceinline__ float dup(float x, float one) {
    float r;
    asm volatile("mul.f32 %0, %1, %2;" : "=f"(r) : "f"(x), "f"(one));
    return r;
}
__device__ __forceinline__ void stsm_x4_t(uint32_t addr, uint32_t r0, uint32_t r1, uint32_t r2, uint32_t r3) {
    asm volatile("stmatrix.sync.aligned.m8n8.x4.trans.shared.b16 [%0], {%1, %2, %3, %4};"
                 ::"r"(addr), "r"(r0), "r"(r1), "r"(r2), "r"(r3) : "memory");
}

struct Ctx {
    uint32_t sbase;
    uint32_t db0;
    uint32_t da0;
    uint32_t empty_tgt;
    bool     signal;
};

template <int N> __device__ __forceinline__ constexpr uint32_t slot_of() { return (3 + N) % NSLOTS; }
template <int N> __device__ __forceinline__ uint32_t phase_of(uint32_t pu) { return pu ^ (((3 + N) / NSLOTS) & 1); }
template <int N> __device__ __forceinline__ void release(const Ctx& cx) {
    if (cx.signal) mbar_arrive_cluster(cx.empty_tgt + slot_of<N>() * 8);
}

enum { FINE, COARSE, COARSE_REG };
template <int N, int MODE>
__device__ __forceinline__ void chunk(float (&acc)[32], const uint32_t (&W)[96], const uint32_t (&A)[16], uint32_t zero,
                                      const Ctx& cx, uint32_t pu, bool& ready) {
    constexpr int KC = N % 6;
    constexpr int B  = slot_of<N>() * 512;
    if (!ready) mbar_wait(cx.sbase + OFF_FULL + slot_of<N>() * 8, phase_of<N>(pu));
    ready = mbar_try(cx.sbase + OFF_FULL + slot_of<N + 1>() * 8, phase_of<N + 1>(pu));
    if (MODE == FINE) {
        wg_fence();
        wgmma_rs<B + 0>(acc, W[KC * 16 + 0],  W[KC * 16 + 1],  W[KC * 16 + 2],  W[KC * 16 + 3], cx.db0);
        wgmma_rs<B + 2>(acc, W[KC * 16 + 4],  W[KC * 16 + 5],  W[KC * 16 + 6],  W[KC * 16 + 7], cx.db0);
        wgmma_rs<B + 4>(acc, W[KC * 16 + 8],  W[KC * 16 + 9],  W[KC * 16 + 10], W[KC * 16 + 11], cx.db0);
        wgmma_rs<B + 6>(acc, W[KC * 16 + 12], W[KC * 16 + 13], W[KC * 16 + 14], W[KC * 16 + 15], cx.db0);
    } else {
        if (MODE == COARSE) {
            wg_fence();
            wgmma_ss<(KC > 0), KC * 4 * 128, B>(acc, cx.da0, cx.db0);
        } else {
            uint32_t a[4];
#pragma unroll
            for (int i = 0; i < 4; i++) asm volatile("xor.b32 %0, %1, %2;" : "=r"(a[i]) : "r"(A[((KC + 2) & 3) * 4 + i]), "r"(zero));
            wg_fence();
            wgmma_rs<B>(acc, a[0], a[1], a[2], a[3], cx.db0);
            wg_commit();
        }
        wgmma_ss<1, (KC * 4 + 1) * 128, B + 2>(acc, cx.da0, cx.db0);
        wgmma_ss<1, (KC * 4 + 2) * 128, B + 4>(acc, cx.da0, cx.db0);
        wgmma_ss<1, (KC * 4 + 3) * 128, B + 6>(acc, cx.da0, cx.db0);
    }
    wg_commit();
    if (KC > 0) {
        wg_wait<1>();
        release<N - (KC > 0)>(cx);
    }
}

__device__ __forceinline__ int seg_row(int g) {
    const int y = g / 12;
    return y * (2 * HW) + (g - y * 12) * 32;
}

template <int NP>
__global__ void __cluster_dims__(2, 1, 1) __launch_bounds__(NTHREADS, 1)
fpn_kernel(Scratch* scr, const __nv_bfloat16* __restrict__ c_ptr, const __nv_bfloat16* __restrict__ p_ptr,
           const int nsteps, const float one, const uint32_t zero,
           const __grid_constant__ CUtensorMap tm_wo, const __grid_constant__ CUtensorMap tm_wl3,
           const __grid_constant__ CUtensorMap tm_p8, const __grid_constant__ CUtensorMap tm_c,
           const __grid_constant__ CUtensorMap tm_p, const __grid_constant__ CUtensorMap tm_out,
           const __grid_constant__ CUtensorMap tm_cf)
{
    extern __shared__ __align__(1024) uint8_t smem[];
    const uint32_t sbase = smem_u32(smem);
    const int tid   = threadIdx.x;
    const int warp  = __shfl_sync(0xffffffffu, tid >> 5, 0);
    const int lane  = tid & 31;
    const int rank  = blockIdx.x & 1;
    const int pair  = blockIdx.x >> 1;
    const int npair = NP ? NP : gridDim.x >> 1;
    const int nfine = NP ? NSEG / (NP ? NP : 1) : nsteps;

    if (tid == 480) {
        prefetch_tmap(&tm_wo); prefetch_tmap(&tm_wl3); prefetch_tmap(&tm_p8);
        prefetch_tmap(&tm_c); prefetch_tmap(&tm_p); prefetch_tmap(&tm_out); prefetch_tmap(&tm_cf);
    }
    if (warp == 12 && elect_one()) {
        for (int s = 0; s < 3; s++) mbar_init(sbase + OFF_FULL + s * 8, 1);
        asm volatile("fence.mbarrier_init.release.cluster;" ::: "memory");
        asm volatile("fence.proxy.async.shared::cta;" ::: "memory");
        const int g0 = pair % 3;
#pragma unroll 1
        for (int s = 0; s < 3; s++) {
            const uint32_t bar = sbase + OFF_FULL + s * 8;
            const uint32_t dst = sbase + OFF_WOUT + g0 * WOUT_SLICE + s * 16384;
            mbar_expect_tx(bar, pair < NJOBS ? 3 * SLOT_BYTES : 2 * SLOT_BYTES);
            tma_load_2d(dst, &tm_wo, rank * 192 + g0 * 64, s * 128, bar);
            if (pair < NJOBS) tma_load_3d(sbase + OFF_RING + s * SLOT_BYTES, &tm_wl3, 0, (pair / 3) * 32, 2 * s, bar);
        }
    }
    if (warp == 13) {
        if (lane == 0) {
            for (int s = 0; s < NSLOTS; s++) {
                if (s >= 3) mbar_init(sbase + OFF_FULL + s * 8, 1);
                mbar_init(sbase + OFF_EMPTY + s * 8, 6);
            }
            mbar_init(sbase + OFF_JB2, 1);
            mbar_init(sbase + OFF_NB, 1);
            asm volatile("st.volatile.shared.u32 [%0], %1;" ::"r"(sbase + OFF_PACE), "r"(6) : "memory");
            asm volatile("fence.mbarrier_init.release.cluster;" ::: "memory");
            asm volatile("fence.proxy.async.shared::cta;" ::: "memory");
        }
        __syncwarp();
        asm volatile("bar.arrive 5, 448;" ::: "memory");
    }
    __syncwarp();
    asm volatile("barrier.cluster.arrive.relaxed.aligned;" ::: "memory");

    if (warp >= 12) {
        asm volatile("setmaxnreg.dec.sync.aligned.u32 32;");
        if (warp == 12) {
            asm volatile("bar.sync 5, 448;" ::: "memory");
            if (elect_one()) {
                const int g1 = (pair + 1) % 3, g2 = (pair + 2) % 3;
#pragma unroll 1
                for (int kc = 0; kc < 6; kc++) {
                    const uint32_t bar = sbase + OFF_FULL + (3 + kc) * 8;
                    mbar_expect_tx(bar, (kc & 1) ? SLOT_BYTES : 5 * SLOT_BYTES);
                    tma_load_5d(sbase + OFF_RING + (3 + kc) * SLOT_BYTES, &tm_p8, kc * 64, pair * 2, 0, bar);
                    if (!(kc & 1)) {
                        tma_load_2d(sbase + OFF_WOUT + g1 * WOUT_SLICE + kc * 8192, &tm_wo, rank * 192 + g1 * 64, kc * 64, bar);
                        tma_load_2d(sbase + OFF_WOUT + g2 * WOUT_SLICE + kc * 8192, &tm_wo, rank * 192 + g2 * 64, kc * 64, bar);
                    }
                }
            }
            __syncwarp();
        }
        asm volatile("barrier.cluster.wait.aligned;" ::: "memory");
        if (warp == 12) {
            const uint32_t dst0 = sbase + OFF_RING + rank * 4096;
            uint32_t so = 9 * 8, ph = 1, step = 6;
            auto next_slot = [&]() {
                so += 8;
                if (so == NSLOTS * 8) { so = 0; ph ^= 1; }
            };
            unsigned mytiles = 0, seen = 0;
            auto look = [&]() {
                asm volatile("ld.relaxed.gpu.global.u32 %0, [%1];" : "=r"(seen) : "l"(&scr->prog) : "memory");
            };
            auto tile = [&](bool coarse, int coord, uint64_t pol, bool last) {
                if (rank == 0 && mytiles >= GOV_START) {
                    const unsigned need = mytiles * npair - 2 * max(GOV_TIGHT - (int)mytiles, 0);
                    unsigned spins = 0;
                    while (__any_sync(0xffffffffu, (int)(need - seen) > 0) && ++spins < 100000u) look();
                }
                mytiles++;
#pragma unroll
                for (int kc = 0; kc < 6; kc++) {
                    const uint32_t bar = sbase + OFF_FULL + so, dst = dst0 + so * (SLOT_BYTES / 8);
                    mbar_wait_bounded(sbase + OFF_EMPTY + so, ph);
                    step++;
                    if (elect_one()) {
                        mbar_expect_tx(bar, SLOT_BYTES);
                        if (coarse) tma_load_5d_mc(dst, &tm_p, kc * 64, pair * 2, coord, bar, pol);
                        else        tma_load_2d_mc(dst, &tm_c, kc * 64, coord, bar, pol);
                        asm volatile("st.volatile.shared.u32 [%0], %1;" ::"r"(sbase + OFF_PACE), "r"(step) : "memory");
                    }
                    if (kc == 0 && rank == 0 && lane == 0 && !last)
                        asm volatile("red.relaxed.gpu.global.add.u32 [%0], 1;" ::"l"(&scr->prog) : "memory");
                    next_slot();
                    if (kc == 3 && rank == 0) look();
                }
            };
#pragma unroll 1
            for (int j = 0; j < nfine; j++) {
                const uint64_t pol = j >= nfine - EF_STEPS ? POLICY_EVICT_FIRST : POLICY_EVICT_NORMAL;
                if ((j & 3) == 0 && j > 0) tile(true, j + 2 * rank, pol, false);
                tile(false, seg_row(j * npair + pair) + rank * HW, pol, j + 1 == nfine);
            }
            if (rank == 0 && lane == 0) {
                if (atomicAdd(&scr->prog, 1u) + 1 == mytiles * npair) {
                    asm volatile("st.relaxed.gpu.global.u32 [%0], 0;" ::"l"(&scr->prog) : "memory");
                    asm volatile("red.relaxed.gpu.global.add.u32 [%0], 1;" ::"l"(&scr->epoch) : "memory");
                }
            }
            __syncwarp();
            for (int s = 0; s < NSLOTS; s++) {
                mbar_wait_bounded(sbase + OFF_EMPTY + so, ph);
                next_slot();
            }
        } else if (warp == 13) {
            auto wait_pace = [&](int need) {
                unsigned spins = 0;
                while (true) {
                    uint32_t v;
                    asm volatile("ld.volatile.shared.u32 %0, [%1];" : "=r"(v) : "r"(sbase + OFF_PACE) : "memory");
                    if ((int)v >= need || ++spins > 4000000u) break;
                    __nanosleep(20);
                }
            };
            if (lane == 0) mbar_expect_tx(sbase + OFF_NB, 12 * 512);
#pragma unroll 1
            for (int k = 0; k < 12; k++) {
                const int j = k < 6 ? 2 : 3;
                wait_pace(PF_FIRST + k * 3 / 4);
                if (lane == 0)
                    tma_load_2d(sbase + OFF_SINK, &tm_cf, 0, (seg_row(j * npair + pair) + rank * HW) * 6 + (k - (j - 2) * 6) * 32,
                                sbase + OFF_NB);
            }
#pragma unroll 1
            for (int i = 5; i < nfine + nfine / 4; i++) {
                const int k5 = i / 5, t = i - k5 * 5;
                const char *b0, *b1;
                if (t == 0) {
                    b0 = (const char*)p_ptr + (size_t)((4 * k5 + 2 * rank) * npair + pair) * (16 * C * 2);
                    b1 = b0 + (size_t)npair * (16 * C * 2);
                } else {
                    b0 = (const char*)c_ptr + (size_t)(seg_row((4 * k5 + t - 1) * npair + pair) + rank * HW) * (C * 2);
                    b1 = b0 + 16 * C * 2;
                }
                wait_pace(6 * i - max(PF_LEAD0 - max(i - PF_DECAY, 0), PF_LEAD));
#pragma unroll
                for (int k = 0; k < 6; k++) {
                    asm volatile("prefetch.global.L2 [%0];" ::"l"((k < 3 ? b0 : b1) + lane * 128 + (k % 3) * 4096) : "memory");
                    __nanosleep(PF_GAP);
                }
            }
            mbar_wait_bounded(sbase + OFF_NB, 0);
        } else if (warp == 15) {
            uint32_t par, v;
            asm volatile("ld.relaxed.gpu.global.u32 %0, [%1];" : "=r"(par) : "l"(&scr->epoch) : "memory");
            uint4* clr = scr->wfrag + (~par & 1) * (6 * NFRAG * 128);
            unsigned spins = 0;
            do {
                __nanosleep(500);
                asm volatile("ld.volatile.shared.u32 %0, [%1];" : "=r"(v) : "r"(sbase + OFF_PACE) : "memory");
            } while (v < CLR_AT && ++spins < 100000u);
            for (int i = blockIdx.x * 32 + lane; i < 6 * NFRAG * 128; i += npair * 64) clr[i] = make_uint4(0u, 0u, 0u, 0u);
        }
    } else {
        uint32_t par;
        asm volatile("ld.relaxed.gpu.global.u32 %0, [%1];" : "=r"(par) : "l"(&scr->epoch) : "memory");
        asm volatile("setmaxnreg.inc.sync.aligned.u32 160;");
        asm volatile("bar.sync 5, 448;" ::: "memory");
        const int wg   = warp >> 2;
        const int wtid = tid & 127;
        Ctx cx;
        cx.sbase     = sbase;
        cx.empty_tgt = mapa(sbase + OFF_EMPTY, warp & 1);
        cx.signal    = (lane == 0) && ((warp & 3) < 2);
        cx.db0       = desc_lo(sbase + OFF_RING);
        cx.da0       = desc_lo(sbase + OFF_WOUT + wg * WOUT_SLICE);
        const int cb = rank * 3 + wg;

        float    acc[32];
        uint32_t qp[16];
        uint32_t W[96];

        {
            uint32_t jph = 0;
            for (int job = pair; job < NJOBS; job += npair) {
                if (job % 3 == wg) {
                    if (job != pair) {
                        named_bar(wg);
                        if (wtid == 0) {
                            mbar_expect_tx(sbase + OFF_JB2, 6 * 4096);
                            for (int s = 0; s < 3; s++)
                                tma_load_3d(sbase + OFF_RING + s * SLOT_BYTES, &tm_wl3, 0, (job / 3) * 32, 2 * s, sbase + OFF_JB2);
                        }
                        for (int kc = 0; kc < 6; kc++) mbar_wait(sbase + OFF_FULL + (3 + kc) * 8, 0);
                        mbar_wait(sbase + OFF_JB2, jph);
                    }
                    float ja[16];
#define JOBK(k) wgmma_ss32<((k) > 0), (k) * 128, ((k) >> 2) * 256 + ((k) & 3) * 2>(ja, cx.da0, cx.db0);
                    mbar_wait(sbase + OFF_FULL, 0);
                    wg_fence();
                    JOBK(0)  JOBK(1)  JOBK(2)  JOBK(3)  JOBK(4)  JOBK(5)  JOBK(6)  JOBK(7)
                    wg_commit();
                    mbar_wait(sbase + OFF_FULL + 8, 0);
                    wg_fence();
                    JOBK(8)  JOBK(9)  JOBK(10) JOBK(11) JOBK(12) JOBK(13) JOBK(14) JOBK(15)
                    wg_commit();
                    mbar_wait(sbase + OFF_FULL + 16, 0);
                    wg_fence();
                    JOBK(16) JOBK(17) JOBK(18) JOBK(19) JOBK(20) JOBK(21) JOBK(22) JOBK(23)
#undef JOBK
                    wg_commit();
                    wg_wait<0>();
                    const int fidx = (cb * NFRAG + (job / 3) * 2) * 128 + wtid;
                    uint4* dst = scr->wfrag + (par & 1) * (6 * NFRAG * 128) + fidx;
#pragma unroll
                    for (int i = 0; i < 2; i++) {
                        asm volatile("st.relaxed.gpu.global.v4.u32 [%0], {%1, %2, %3, %4};" ::"l"(dst + i * 128),
                                     "r"(pack_neg(ja[8 * i + 0], ja[8 * i + 1])), "r"(pack_neg(ja[8 * i + 2], ja[8 * i + 3])),
                                     "r"(pack_neg(ja[8 * i + 4], ja[8 * i + 5])), "r"(pack_neg(ja[8 * i + 6], ja[8 * i + 7])) : "memory");
                    }
                }
                if (job + npair < NJOBS) asm volatile("bar.sync 4, 384;" ::: "memory");
                if (job != pair) jph ^= 1;
            }
        }

        par &= 1;
        if (pair < NJOBS) asm volatile("bar.sync 6, 384;" ::: "memory");
        asm volatile("barrier.cluster.wait.aligned;" ::: "memory");

        mbar_wait(sbase + OFF_FULL, 0);
        mbar_wait(sbase + OFF_FULL + 8, 0);
        mbar_wait(sbase + OFF_FULL + 16, 0);
        if (cx.signal) {
            mbar_arrive_cluster(cx.empty_tgt);
            mbar_arrive_cluster(cx.empty_tgt + 8);
            mbar_arrive_cluster(cx.empty_tgt + 16);
        }
        auto pack_q = [&]() {
            uint32_t all = 0;
#pragma unroll
            for (int i = 0; i < 16; i++) {
                qp[i] = pack_bf16(acc[2 * i], acc[2 * i + 1]);
                if (i >= 4) all |= qp[i];
            }
            qp[3] |= all & zero;
        };
        bool ready = false;
        uint32_t pu = 0;
#define CHUNK(N, MODE) chunk<N, MODE>(acc, W, qp, zero, cx, pu, ready)

        const uint4* wsrc = scr->wfrag + (par * 6 + cb) * (NFRAG * 128) + wtid;
        auto load_w = [&](int kc) {
#pragma unroll
            for (int s = 4 * kc; s < 4 * kc + 4; s++) {
                asm volatile("ld.relaxed.gpu.global.v4.u32 {%0, %1, %2, %3}, [%4];"
                             : "=r"(W[4 * s]), "=r"(W[4 * s + 1]), "=r"(W[4 * s + 2]), "=r"(W[4 * s + 3])
                             : "l"(wsrc + s * 128) : "memory");
            }
        };
        auto check_w = [&](int kc) {
            uint32_t* w = kc < 6 ? W + 16 * kc : qp;
            asm volatile(
                "{\n.reg .pred p;\n.reg .u32 m, n;\n"
                "mov.u32 n, 0;\n"
                "CHK_%=:\n"
                "mov.u32 m, %%clock;\n or.b32 m, m, 1;\n min.u32 m, m, %0;\n"
                "min.u32 m, m, %1;\n min.u32 m, m, %2;\n min.u32 m, m, %3;\n min.u32 m, m, %4;\n min.u32 m, m, %5;\n"
                "min.u32 m, m, %6;\n min.u32 m, m, %7;\n min.u32 m, m, %8;\n min.u32 m, m, %9;\n min.u32 m, m, %10;\n"
                "min.u32 m, m, %11;\n min.u32 m, m, %12;\n min.u32 m, m, %13;\n min.u32 m, m, %14;\n min.u32 m, m, %15;\n"
                "setp.ne.u32 p, m, 0;\n"
                "vote.sync.all.pred p, p, 0xffffffff;\n"
                "@p bra.uni OK_%=;\n"
                "add.u32 n, n, 1;\n"
                "setp.gt.u32 p, n, 5000000;\n"
                "@p bra.uni OK_%=;\n"
                "ld.relaxed.gpu.global.v4.u32 {%0, %1, %2, %3}, [%16];\n"
                "ld.relaxed.gpu.global.v4.u32 {%4, %5, %6, %7}, [%16 + 2048];\n"
                "ld.relaxed.gpu.global.v4.u32 {%8, %9, %10, %11}, [%16 + 4096];\n"
                "ld.relaxed.gpu.global.v4.u32 {%12, %13, %14, %15}, [%16 + 6144];\n"
                "bra.uni CHK_%=;\n"
                "OK_%=:\n}"
                : "+r"(w[0]), "+r"(w[1]), "+r"(w[2]), "+r"(w[3]), "+r"(w[4]), "+r"(w[5]), "+r"(w[6]), "+r"(w[7]),
                  "+r"(w[8]), "+r"(w[9]), "+r"(w[10]), "+r"(w[11]), "+r"(w[12]), "+r"(w[13]), "+r"(w[14]), "+r"(w[15])
                : "l"(wsrc + kc * 512) : "memory");
        };
        const uint32_t stage = sbase + OFF_WOUT + wg * WOUT_SLICE + 2 * 8192;
        const uint32_t st_addr = stage + (((lane >> 4) * 8 + (lane & 7)) << 7)
                               + (((((warp & 3) << 1) | ((lane >> 3) & 1)) ^ (lane & 7)) << 4);
        auto publish = [&](int s) {
            if (pair == (NJOBS + s) % npair) {
                uint32_t a[4];
                asm volatile("ldmatrix.sync.aligned.m8n8.x4.trans.shared.b16 {%0, %1, %2, %3}, [%4];"
                             : "=r"(a[0]), "=r"(a[1]), "=r"(a[2]), "=r"(a[3]) : "r"(st_addr + s * 8192) : "memory");
                asm volatile("st.relaxed.gpu.global.v4.u32 [%0], {%1, %2, %3, %4};" ::"l"(wsrc + (24 + s) * 128),
                             "r"(enc_neg(a[0])), "r"(enc_neg(a[1])), "r"(enc_neg(a[2])), "r"(enc_neg(a[3])) : "memory");
            }
        };
        CHUNK(0, COARSE);
        CHUNK(1, COARSE);
        CHUNK(2, COARSE);
        publish(0);
        load_w(0);
        CHUNK(3, COARSE);
        publish(1);
        load_w(1);
        CHUNK(4, COARSE);
        publish(2);
        load_w(2);
        CHUNK(5, COARSE);
        publish(3);
        wg_wait<0>();
        release<5>(cx);
        pack_q();

        auto flush_part = [&](int row, int part) {
            if (part == 0) {
                asm volatile("fence.proxy.async.shared::cta;" ::: "memory");
                named_bar(wg);
            }
            if (wtid == 0) {
                tma_store_2d(&tm_out, cb * 64, row + (part >> 1) * HW + (part & 1) * 16, stage + part * 8192, POLICY_EVICT_FIRST);
                if (part == 3) asm volatile("cp.async.bulk.commit_group;" ::: "memory");
            }
        };
        auto init_acc = [&](int t) {
#pragma unroll
            for (int b = 0; b < 2; b++) {
#pragma unroll
                for (int h = 0; h < 2; h++) {
                    const uint32_t q = qp[t * 4 + b * 2 + h];
                    const float lo = __uint_as_float(q << 16), hi = __uint_as_float(q & 0xffff0000u);
#pragma unroll
                    for (int dy = 0; dy < 2; dy++) {
                        acc[16 * dy + 8 * b + 2 * h]         = dy ? dup(lo, one) : lo;
                        acc[16 * dy + 8 * b + 2 * h + 1]     = dup(lo, one);
                        acc[16 * dy + 8 * b + 4 + 2 * h]     = dy ? dup(hi, one) : hi;
                        acc[16 * dy + 8 * b + 4 + 2 * h + 1] = dup(hi, one);
                    }
                }
            }
        };
        auto stage_tile = [&](int slot) {
            if (wtid == 0) asm volatile("cp.async.bulk.wait_group.read 0;" ::: "memory");
            named_bar(wg);
            wg_wait<0>();
            if (cx.signal) mbar_arrive_cluster(cx.empty_tgt + slot * 8);
#pragma unroll
            for (int i = 0; i < 8; i += 2) {
                stsm_x4_t(st_addr + i * 4096,
                          pack_bf16(acc[4 * i + 0], acc[4 * i + 1]), pack_bf16(acc[4 * i + 2], acc[4 * i + 3]),
                          pack_bf16(acc[4 * i + 4], acc[4 * i + 5]), pack_bf16(acc[4 * i + 6], acc[4 * i + 7]));
            }
        };

        auto load_wo = [&]() {
#pragma unroll
            for (int s = 0; s < 4; s++) {
                asm volatile("ld.global.ca.v4.u32 {%0, %1, %2, %3}, [%4];"
                             : "=r"(qp[4 * s]), "=r"(qp[4 * s + 1]), "=r"(qp[4 * s + 2]), "=r"(qp[4 * s + 3])
                             : "l"(wsrc + (24 + s) * 128) : "memory");
            }
        };

        init_acc(0);
        check_w(0);
        load_w(3);
        load_w(4);
        CHUNK(6, FINE);
        check_w(1);
        CHUNK(7, FINE);
        check_w(2);
        CHUNK(8, FINE);
        check_w(3);
        load_w(5);
        CHUNK(9, FINE);
        check_w(4);
        CHUNK(10, FINE);
        check_w(5);
        CHUNK(11, FINE);

        int seg = pair;
        int prow = seg_row(seg);
        while (true) {
            stage_tile(slot_of<11>());
            init_acc(1);
            CHUNK(12, FINE);
            flush_part(prow, 0);
            CHUNK(13, FINE);
            CHUNK(14, FINE);
            flush_part(prow, 1);
            CHUNK(15, FINE);
            flush_part(prow, 2);
            CHUNK(16, FINE);
            flush_part(prow, 3);
            CHUNK(17, FINE);
            seg += npair;
            prow = seg_row(seg);
            stage_tile(slot_of<17>());
            init_acc(2);
            CHUNK(18, FINE);
            flush_part(prow, 0);
            CHUNK(19, FINE);
            CHUNK(20, FINE);
            flush_part(prow, 1);
            CHUNK(21, FINE);
            flush_part(prow, 2);
            CHUNK(22, FINE);
            flush_part(prow, 3);
            CHUNK(23, FINE);
            seg += npair;
            prow = seg_row(seg);
            stage_tile(slot_of<23>());
            init_acc(3);
            CHUNK(24, FINE);
            flush_part(prow, 0);
            CHUNK(25, FINE);
            load_wo();
            CHUNK(26, FINE);
            flush_part(prow, 1);
            CHUNK(27, FINE);
            flush_part(prow, 2);
            CHUNK(28, FINE);
            flush_part(prow, 3);
            CHUNK(29, FINE);
            seg += npair;
            prow = seg_row(seg);
            if (seg + npair >= NSEG) break;
            stage_tile(slot_of<29>());
            CHUNK(30, COARSE);
            flush_part(prow, 0);
            CHUNK(31, COARSE);
            check_w(6);
            CHUNK(32, COARSE_REG);
            CHUNK(33, COARSE_REG);
            flush_part(prow, 1);
            CHUNK(34, COARSE_REG);
            CHUNK(35, COARSE_REG);
            wg_wait<0>();
            release<35>(cx);
            pack_q();
            init_acc(0);
            CHUNK(36, FINE);
            flush_part(prow, 2);
            CHUNK(37, FINE);
            CHUNK(38, FINE);
            CHUNK(39, FINE);
            flush_part(prow, 3);
            CHUNK(40, FINE);
            CHUNK(41, FINE);
            seg += npair;
            prow = seg_row(seg);
            pu ^= 1;
        }
#undef CHUNK
        stage_tile(slot_of<29>());
#pragma unroll
        for (int part = 0; part < 4; part++) flush_part(prow, part);
        if (wtid == 0) asm volatile("cp.async.bulk.wait_group.read 0;" ::: "memory");
    }
}

typedef CUresult (*EncodeFn)(CUtensorMap*, CUtensorMapDataType, cuuint32_t, void*, const cuuint64_t*, const cuuint64_t*,
                             const cuuint32_t*, const cuuint32_t*, CUtensorMapInterleave, CUtensorMapSwizzle,
                             CUtensorMapL2promotion, CUtensorMapFloatOOBfill);

void encode(EncodeFn fn, CUtensorMap* tm, const void* ptr, int rank, const cuuint64_t* dims, const cuuint64_t* strides,
            const cuuint32_t* box, CUtensorMapSwizzle swizzle = CU_TENSOR_MAP_SWIZZLE_128B,
            CUtensorMapL2promotion promotion = CU_TENSOR_MAP_L2_PROMOTION_NONE) {
    const cuuint32_t es[5] = {1, 1, 1, 1, 1};
    fn(tm, CU_TENSOR_MAP_DATA_TYPE_BFLOAT16, (cuuint32_t)rank, const_cast<void*>(ptr), dims, strides, box, es,
       CU_TENSOR_MAP_INTERLEAVE_NONE, swizzle, promotion, CU_TENSOR_MAP_FLOAT_OOB_FILL_NONE);
}

}

extern "C" void kernel_launch(void* const* d_in, const int* in_sizes, int n_in, void* d_out, int out_size) {
    (void)in_sizes; (void)n_in; (void)out_size;
    const __nv_bfloat16* c_fine   = (const __nv_bfloat16*)d_in[0];
    const __nv_bfloat16* p_coarse = (const __nv_bfloat16*)d_in[1];
    const __nv_bfloat16* w_lat    = (const __nv_bfloat16*)d_in[2];
    const __nv_bfloat16* w_out    = (const __nv_bfloat16*)d_in[3];

    static EncodeFn fn = nullptr;
    static int np = 0;
    static Scratch* scr = nullptr;
    if (!fn) {
        void* p = nullptr;
        cudaDriverEntryPointQueryResult qr;
        cudaGetDriverEntryPoint("cuTensorMapEncodeTiled", &p, cudaEnableDefault, &qr);
        fn = (EncodeFn)p;
        cudaGetSymbolAddress((void**)&scr, g_scratch);
        cudaFuncSetAttribute(fpn_kernel<NPAIRS>, cudaFuncAttributeMaxDynamicSharedMemorySize, SMEM_BYTES);
        cudaFuncSetAttribute(fpn_kernel<0>, cudaFuncAttributeMaxDynamicSharedMemorySize, SMEM_BYTES);
        cudaLaunchConfig_t cfg = {};
        cfg.gridDim = dim3(2); cfg.blockDim = dim3(NTHREADS); cfg.dynamicSmemBytes = SMEM_BYTES;
        cudaLaunchAttribute at[1];
        at[0].id = cudaLaunchAttributeClusterDimension;
        at[0].val.clusterDim.x = 2; at[0].val.clusterDim.y = 1; at[0].val.clusterDim.z = 1;
        cfg.attrs = at; cfg.numAttrs = 1;
        if (cudaOccupancyMaxActiveClusters(&np, fpn_kernel<0>, &cfg) != cudaSuccess || np < 1) np = 1;
        if (np > NPAIRS) np = NPAIRS;
        while ((NSEG / 4) % np) np--;
    }

    CUtensorMap tm_cf, tm_c, tm_p, tm_wl3, tm_out, tm_p8, tm_wo;
    {
        const cuuint64_t dims[2] = {(cuuint64_t)C, (cuuint64_t)NPIX};
        const cuuint64_t str[1]  = {(cuuint64_t)C * 2};
        const cuuint32_t box_in[2]  = {64, 32};
        const cuuint32_t box_out[2] = {64, 16};
        encode(fn, &tm_c, c_fine, 2, dims, str, box_in);
        encode(fn, &tm_out, d_out, 2, dims, str, box_out);
    }
    {
        const cuuint64_t dims[5] = {(cuuint64_t)C, 2, 4, (cuuint64_t)(2 * np), (cuuint64_t)(NSEG / np)};
        const cuuint64_t str[4]  = {(cuuint64_t)4 * C * 2, (cuuint64_t)C * 2, (cuuint64_t)8 * C * 2, (cuuint64_t)np * 16 * C * 2};
        const cuuint32_t box[5]  = {64, 2, 4, 2, 2};
        encode(fn, &tm_p, p_coarse, 5, dims, str, box);
        const cuuint32_t box8[5] = {64, 2, 4, 2, 4};
        encode(fn, &tm_p8, p_coarse, 5, dims, str, box8);
    }
    {
        const cuuint64_t dims[2] = {(cuuint64_t)C, (cuuint64_t)C};
        const cuuint64_t str[1]  = {(cuuint64_t)C * 2};
        const cuuint32_t box[2] = {64, 128};
        encode(fn, &tm_wo, w_out, 2, dims, str, box);
    }
    {
        const cuuint64_t dims[3] = {64, (cuuint64_t)C, 6};
        const cuuint64_t str[2]  = {(cuuint64_t)C * 2, 128};
        const cuuint32_t box[3]  = {64, 32, 2};
        encode(fn, &tm_wl3, w_lat, 3, dims, str, box);
    }
    {
        const cuuint64_t dims[2] = {64, (cuuint64_t)NPIX * 6};
        const cuuint64_t str[1]  = {128};
        const cuuint32_t box[2]  = {8, 32};
        encode(fn, &tm_cf, c_fine, 2, dims, str, box, CU_TENSOR_MAP_SWIZZLE_NONE, CU_TENSOR_MAP_L2_PROMOTION_L2_128B);
    }
    auto kernel = np == NPAIRS ? fpn_kernel<NPAIRS> : fpn_kernel<0>;
    kernel<<<2 * np, NTHREADS, SMEM_BYTES>>>(scr, c_fine, p_coarse, NSEG / np, 1.0f, 0u,
                                             tm_wo, tm_wl3, tm_p8, tm_c, tm_p, tm_out, tm_cf);
}
```

```cpp
#include <cuda_runtime.h>
#include <cuda_bf16.h>
#include <cuda.h>
#include <stdint.h>

namespace {

constexpr int C          = 384;
constexpr int HW         = 384;
constexpr int NPIX       = HW * HW;
constexpr int NSEG       = NPIX / 64;
constexpr int NJOBS      = 36;

constexpr int NFRAG      = 28;
constexpr int NSLOTS     = 10;
constexpr int NPAIRS     = 64;
constexpr int PF_LEAD    = 5;
constexpr int PF_LEAD0   = 18;
constexpr int PF_DECAY   = 12;
constexpr int PF_FIRST   = 11;
constexpr int PF_GAP     = 50;
constexpr int GOV_START  = 10;
constexpr int GOV_TIGHT  = 24;
constexpr int EF_STEPS   = 9;
constexpr int SKEW_UNITS = 2;
constexpr int CLR_AT     = 20;

constexpr int SLOT_BYTES  = 8192;
constexpr int WOUT_SLICE  = 384 * 128;
constexpr int OFF_WOUT    = 0;
constexpr int OFF_RING    = 3 * WOUT_SLICE;
constexpr int OFF_FULL    = OFF_RING + NSLOTS * SLOT_BYTES;
constexpr int OFF_EMPTY   = OFF_FULL + 8 * NSLOTS;
constexpr int OFF_JB2     = OFF_EMPTY + 8 * NSLOTS;
constexpr int OFF_PACE    = OFF_JB2 + 8;
constexpr int OFF_NB      = OFF_PACE + 8;
constexpr int OFF_SINK    = (OFF_NB + 8 + 127) / 128 * 128;
constexpr int SMEM_BYTES  = OFF_SINK + 512;
static_assert(SMEM_BYTES <= 232448, "smem");
static_assert(NSLOTS == 10, "a unit (30 ring items) must be an odd number of rounds of the ring");

constexpr int      SMEM_BASE = 1024;
constexpr uint64_t DESC_RING = 0x4000004000010000ull + ((SMEM_BASE + OFF_RING) >> 4);

constexpr int NTHREADS = 512;
constexpr uint64_t POLICY_EVICT_FIRST  = 0x12F0000000000000ull;
constexpr uint64_t POLICY_EVICT_NORMAL = 0x1000000000000000ull;

struct Scratch {
    uint4    wfrag[2 * 6 * NFRAG * 128];
    unsigned epoch;
    unsigned pad0[31];
    unsigned prog;
};
__device__ Scratch g_scratch;

__device__ __forceinline__ uint32_t smem_u32(const void* p) { return (uint32_t)__cvta_generic_to_shared(p); }

__device__ __forceinline__ void mbar_init(uint32_t bar, uint32_t cnt) {
    asm volatile("mbarrier.init.shared::cta.b64 [%0], %1;" ::"r"(bar), "r"(cnt) : "memory");
}
__device__ __forceinline__ void mbar_expect_tx(uint32_t bar, uint32_t bytes) {
    asm volatile("mbarrier.arrive.expect_tx.shared::cta.b64 _, [%0], %1;" ::"r"(bar), "r"(bytes) : "memory");
}
__device__ __forceinline__ void mbar_wait_bounded(uint32_t bar, uint32_t parity) {
    asm volatile(
        "{\n"
        ".reg .pred p;\n"
        ".reg .u32 n;\n"
        "mbarrier.try_wait.parity.shared::cta.b64 p, [%0], %1;\n"
        "@p bra DONE_%=;\n"
        "mov.u32 n, 0;\n"
        "WAIT_%=:\n"
        "mbarrier.try_wait.parity.shared::cta.b64 p, [%0], %1;\n"
        "@p bra DONE_%=;\n"
        "add.u32 n, n, 1;\n"
        "setp.lt.u32 p, n, 4000000;\n"
        "@p bra WAIT_%=;\n"
        "trap;\n"
        "DONE_%=:\n"
        "}\n" ::"r"(bar), "r"(parity) : "memory");
}
__device__ __forceinline__ void mbar_wait(uint32_t bar, uint32_t parity) {
    asm volatile(
        "{\n"
        ".reg .pred p;\n"
        "WAIT_%=:\n"
        "mbarrier.try_wait.parity.shared::cta.b64 p, [%0], %1;\n"
        "@!p bra WAIT_%=;\n"
        "}\n" ::"r"(bar), "r"(parity) : "memory");
}
__device__ __forceinline__ bool mbar_try(uint32_t bar, uint32_t parity) {
    uint32_t r;
    asm volatile("{\n.reg .pred p;\nmbarrier.test_wait.parity.shared::cta.b64 p, [%1], %2;\nselp.u32 %0, 1, 0, p;\n}\n"
                 : "=r"(r) : "r"(bar), "r"(parity) : "memory");
    return r != 0;
}
__device__ __forceinline__ void mbar_arrive_cluster(uint32_t cluster_addr) {
    asm volatile("mbarrier.arrive.shared::cluster.b64 _, [%0];" ::"r"(cluster_addr) : "memory");
}
__device__ __forceinline__ uint32_t mapa(uint32_t addr, uint32_t rank) {
    uint32_t r;
    asm("mapa.shared::cluster.u32 %0, %1, %2;" : "=r"(r) : "r"(addr), "r"(rank));
    return r;
}
__device__ __forceinline__ void named_bar(int wg) {
    asm volatile("bar.sync %0, 128;" ::"r"(wg + 1) : "memory");
}

__device__ __forceinline__ void tma_load_2d(uint32_t dst, const CUtensorMap* tm, int c0, int c1, uint32_t bar) {
    asm volatile("cp.async.bulk.tensor.2d.shared::cluster.global.mbarrier::complete_tx::bytes [%0], [%1, {%2, %3}], [%4];"
                 ::"r"(dst), "l"(tm), "r"(c0), "r"(c1), "r"(bar) : "memory");
}
__device__ __forceinline__ void tma_load_3d(uint32_t dst, const CUtensorMap* tm, int c0, int c1, int c2, uint32_t bar) {
    asm volatile("cp.async.bulk.tensor.3d.shared::cluster.global.mbarrier::complete_tx::bytes [%0], [%1, {%2, %3, %4}], [%5];"
                 ::"r"(dst), "l"(tm), "r"(c0), "r"(c1), "r"(c2), "r"(bar) : "memory");
}
__device__ __forceinline__ void tma_load_5d(uint32_t dst, const CUtensorMap* tm, int c0, int c3, int c4, uint32_t bar) {
    asm volatile("cp.async.bulk.tensor.5d.shared::cluster.global.mbarrier::complete_tx::bytes [%0], [%1, {%2, 0, 0, %3, %4}], [%5];"
                 ::"r"(dst), "l"(tm), "r"(c0), "r"(c3), "r"(c4), "r"(bar) : "memory");
}
__device__ __forceinline__ void tma_load_2d_mc(uint32_t dst, const CUtensorMap* tm, int c0, int c1, uint32_t bar, uint64_t pol) {
    asm volatile("cp.async.bulk.tensor.2d.shared::cluster.global.mbarrier::complete_tx::bytes.multicast::cluster.L2::cache_hint"
                 " [%0], [%1, {%2, %3}], [%4], %5, %6;"
                 ::"r"(dst), "l"(tm), "r"(c0), "r"(c1), "r"(bar), "h"((uint16_t)3), "l"(pol) : "memory");
}
__device__ __forceinline__ void tma_load_5d_mc(uint32_t dst, const CUtensorMap* tm, int c0, int c3, int c4, uint32_t bar, uint64_t pol) {
    asm volatile("cp.async.bulk.tensor.5d.shared::cluster.global.mbarrier::complete_tx::bytes.multicast::cluster.L2::cache_hint"
                 " [%0], [%1, {%2, 0, 0, %3, %4}], [%5], %6, %7;"
                 ::"r"(dst), "l"(tm), "r"(c0), "r"(c3), "r"(c4), "r"(bar), "h"((uint16_t)3), "l"(pol) : "memory");
}
__device__ __forceinline__ void tma_store_2d(const CUtensorMap* tm, int c0, int c1, uint32_t src, uint64_t pol) {
    asm volatile("cp.async.bulk.tensor.2d.global.shared::cta.bulk_group.L2::cache_hint [%0, {%1, %2}], [%3], %4;"
                 ::"l"(tm), "r"(c0), "r"(c1), "r"(src), "l"(pol) : "memory");
}
__device__ __forceinline__ bool elect_one() {
    uint32_t r;
    asm volatile("{\n.reg .pred p;\nelect.sync _|p, 0xffffffff;\nselp.u32 %0, 1, 0, p;\n}" : "=r"(r));
    return r != 0;
}
__device__ __forceinline__ void prefetch_tmap(const CUtensorMap* tm) {
    asm volatile("prefetch.tensormap [%0];" ::"l"(tm) : "memory");
}

__device__ __forceinline__ void wg_fence()  { asm volatile("wgmma.fence.sync.aligned;" ::: "memory"); }
__device__ __forceinline__ void wg_commit() { asm volatile("wgmma.commit_group.sync.aligned;" ::: "memory"); }
template <int N> __device__ __forceinline__ void wg_wait() { asm volatile("wgmma.wait_group.sync.aligned %0;" ::"n"(N) : "memory"); }

#define ACC16(a)                                                                                              \
    "+f"(a[0]), "+f"(a[1]), "+f"(a[2]), "+f"(a[3]), "+f"(a[4]), "+f"(a[5]), "+f"(a[6]), "+f"(a[7]),           \
    "+f"(a[8]), "+f"(a[9]), "+f"(a[10]), "+f"(a[11]), "+f"(a[12]), "+f"(a[13]), "+f"(a[14]), "+f"(a[15])
#define ACC32(a)                                                                                              \
    ACC16(a),                                                                                                 \
    "+f"(a[16]), "+f"(a[17]), "+f"(a[18]), "+f"(a[19]), "+f"(a[20]), "+f"(a[21]), "+f"(a[22]), "+f"(a[23]),   \
    "+f"(a[24]), "+f"(a[25]), "+f"(a[26]), "+f"(a[27]), "+f"(a[28]), "+f"(a[29]), "+f"(a[30]), "+f"(a[31])
#define ACC16_STR "{%0, %1, %2, %3, %4, %5, %6, %7, %8, %9, %10, %11, %12, %13, %14, %15}"
#define ACC32_STR                                                                                             \
    "{%0, %1, %2, %3, %4, %5, %6, %7, %8, %9, %10, %11, %12, %13, %14, %15, "                                 \
    "%16, %17, %18, %19, %20, %21, %22, %23, %24, %25, %26, %27, %28, %29, %30, %31}"

template <int BOFF>
__device__ __forceinline__ void wgmma_rs(float (&d)[32], uint32_t a0, uint32_t a1, uint32_t a2, uint32_t a3) {
    asm volatile("{\n.reg .b64 db;\n"
                 "mov.b64 db, %36;\n"
                 "wgmma.mma_async.sync.aligned.m64n64k16.f32.bf16.bf16 " ACC32_STR
                 ", {%32, %33, %34, %35}, db, 1, -1, 1, 0;\n}"
                 : ACC32(d) : "r"(a0), "r"(a1), "r"(a2), "r"(a3), "n"(DESC_RING + BOFF));
}
template <int ACCUM, int AOFF, int BOFF>
__device__ __forceinline__ void wgmma_ss(float (&d)[32], uint32_t da_lo) {
    asm volatile("{\n.reg .b64 da, db;\n.reg .b32 lo;\n"
                 "add.u32 lo, %32, %34;\nmov.b64 da, {lo, 0x40000040};\n"
                 "mov.b64 db, %35;\n"
                 "wgmma.mma_async.sync.aligned.m64n64k16.f32.bf16.bf16 " ACC32_STR
                 ", da, db, %33, 1, 1, 1, 0;\n}"
                 : ACC32(d) : "r"(da_lo), "n"(ACCUM), "n"(AOFF), "n"(DESC_RING + BOFF));
}
template <int ACCUM, int AOFF, int BOFF>
__device__ __forceinline__ void wgmma_ss32(float (&d)[16], uint32_t da_lo) {
    asm volatile("{\n.reg .b64 da, db;\n.reg .b32 lo;\n"
                 "add.u32 lo, %16, %18;\nmov.b64 da, {lo, 0x40000040};\n"
                 "mov.b64 db, %19;\n"
                 "wgmma.mma_async.sync.aligned.m64n32k16.f32.bf16.bf16 " ACC16_STR
                 ", da, db, %17, 1, 1, 1, 0;\n}"
                 : ACC16(d) : "r"(da_lo), "n"(ACCUM), "n"(AOFF), "n"(DESC_RING + BOFF));
}
__device__ __forceinline__ uint32_t desc_lo(uint32_t addr) { return ((addr & 0x3FFFFu) >> 4) | (1u << 16); }
__device__ __forceinline__ uint32_t pack_bf16(float lo, float hi) {
    uint32_t r;
    asm("cvt.rn.bf16x2.f32 %0, %1, %2;" : "=r"(r) : "f"(hi), "f"(lo));
    return r;
}
__device__ __forceinline__ uint32_t enc_neg(uint32_t pair) {
    const uint32_t v = pair ^ 0x80008000u;
    return v == 0u ? 0x80008000u : v;
}
__device__ __forceinline__ uint32_t pack_neg(float lo, float hi) { return enc_neg(pack_bf16(lo, hi)); }
__device__ __forceinline__ float dup(float x, float one) {
    float r;
    asm volatile("mul.f32 %0, %1, %2;" : "=f"(r) : "f"(x), "f"(one));
    return r;
}
__device__ __forceinline__ void stsm_x4_t(uint32_t addr, uint32_t r0, uint32_t r1, uint32_t r2, uint32_t r3) {
    asm volatile("stmatrix.sync.aligned.m8n8.x4.trans.shared.b16 [%0], {%1, %2, %3, %4};"
                 ::"r"(addr), "r"(r0), "r"(r1), "r"(r2), "r"(r3) : "memory");
}

struct Ctx {
    uint32_t sbase;
    uint32_t da0;
    uint32_t empty_tgt;
    bool     signal;
};

template <int N> __device__ __forceinline__ constexpr uint32_t slot_of() { return (3 + N) % NSLOTS; }
template <int N> __device__ __forceinline__ uint32_t phase_of(uint32_t pu) { return pu ^ (((3 + N) / NSLOTS) & 1); }
template <int N> __device__ __forceinline__ void release(const Ctx& cx) {
    if (cx.signal) mbar_arrive_cluster(cx.empty_tgt + slot_of<N>() * 8);
}

enum { FINE, COARSE, COARSE_REG };
template <int N, int MODE>
__device__ __forceinline__ void chunk(float (&acc)[32], const uint32_t (&W)[96], const uint32_t (&A)[16], uint32_t zero,
                                      const Ctx& cx, uint32_t pu, bool& ready, int turn) {
    constexpr int KC = N % 6;
    constexpr int B  = slot_of<N>() * 512;
    if (!ready) mbar_wait(cx.sbase + OFF_FULL + slot_of<N>() * 8, phase_of<N>(pu));
    ready = mbar_try(cx.sbase + OFF_FULL + slot_of<N + 1>() * 8, phase_of<N + 1>(pu));
    if (N >= 12 && turn >= 0) {
        const int id = 8 + (((N / 6) ^ pu) & 1) * 4 + turn;
        if (KC == 2 && turn > 0) asm volatile("bar.sync %0, 256;" ::"r"(id - 1) : "memory");
        if (KC == 4 && turn < 2) asm volatile("bar.arrive %0, 256;" ::"r"(id) : "memory");
    }
    if (MODE == FINE) {
        wg_fence();
        wgmma_rs<B + 0>(acc, W[KC * 16 + 0],  W[KC * 16 + 1],  W[KC * 16 + 2],  W[KC * 16 + 3]);
        wgmma_rs<B + 2>(acc, W[KC * 16 + 4],  W[KC * 16 + 5],  W[KC * 16 + 6],  W[KC * 16 + 7]);
        wgmma_rs<B + 4>(acc, W[KC * 16 + 8],  W[KC * 16 + 9],  W[KC * 16 + 10], W[KC * 16 + 11]);
        wgmma_rs<B + 6>(acc, W[KC * 16 + 12], W[KC * 16 + 13], W[KC * 16 + 14], W[KC * 16 + 15]);
    } else {
        if (MODE == COARSE) {
            wg_fence();
            wgmma_ss<(KC > 0), KC * 4 * 128, B>(acc, cx.da0);
        } else {
            uint32_t a[4];
#pragma unroll
            for (int i = 0; i < 4; i++) asm volatile("xor.b32 %0, %1, %2;" : "=r"(a[i]) : "r"(A[((KC + 2) & 3) * 4 + i]), "r"(zero));
            wg_fence();
            wgmma_rs<B>(acc, a[0], a[1], a[2], a[3]);
            wg_commit();
        }
        wgmma_ss<1, (KC * 4 + 1) * 128, B + 2>(acc, cx.da0);
        wgmma_ss<1, (KC * 4 + 2) * 128, B + 4>(acc, cx.da0);
        wgmma_ss<1, (KC * 4 + 3) * 128, B + 6>(acc, cx.da0);
    }
    wg_commit();
    if (KC > 0) {
        wg_wait<1>();
        release<N - (KC > 0)>(cx);
    }
}

__device__ __forceinline__ int seg_row(int g) {
    const int y = g / 12;
    return y * (2 * HW) + (g - y * 12) * 32;
}

template <int NP>
__global__ void __cluster_dims__(2, 1, 1) __launch_bounds__(NTHREADS, 1)
fpn_kernel(Scratch* scr, const __nv_bfloat16* __restrict__ c_ptr, const __nv_bfloat16* __restrict__ p_ptr,
           const int nsteps, const float one, const uint32_t zero,
           const __grid_constant__ CUtensorMap tm_wo, const __grid_constant__ CUtensorMap tm_wl3,
           const __grid_constant__ CUtensorMap tm_p8, const __grid_constant__ CUtensorMap tm_c,
           const __grid_constant__ CUtensorMap tm_p, const __grid_constant__ CUtensorMap tm_out,
           const __grid_constant__ CUtensorMap tm_cf)
{
    extern __shared__ __align__(1024) uint8_t smem[];
    const uint32_t sbase = smem_u32(smem);
    const int tid   = threadIdx.x;
    const int warp  = __shfl_sync(0xffffffffu, tid >> 5, 0);
    const int lane  = tid & 31;
    const int rank  = blockIdx.x & 1;
    const int pair  = blockIdx.x >> 1;
    const int npair = NP ? NP : gridDim.x >> 1;
    const int nfine = NP ? NSEG / (NP ? NP : 1) : nsteps;

    if (tid == 480) {
        prefetch_tmap(&tm_wo); prefetch_tmap(&tm_wl3); prefetch_tmap(&tm_p8);
        prefetch_tmap(&tm_c); prefetch_tmap(&tm_p); prefetch_tmap(&tm_out); prefetch_tmap(&tm_cf);
    }
    if (warp == 12 && elect_one()) {
        for (int s = 0; s < 3; s++) mbar_init(sbase + OFF_FULL + s * 8, 1);
        asm volatile("fence.mbarrier_init.release.cluster;" ::: "memory");
        asm volatile("fence.proxy.async.shared::cta;" ::: "memory");
        const int g0 = pair % 3;
#pragma unroll 1
        for (int s = 0; s < 3; s++) {
            const uint32_t bar = sbase + OFF_FULL + s * 8;
            const uint32_t dst = sbase + OFF_WOUT + g0 * WOUT_SLICE + s * 16384;
            mbar_expect_tx(bar, pair < NJOBS ? 3 * SLOT_BYTES : 2 * SLOT_BYTES);
            tma_load_2d(dst, &tm_wo, rank * 192 + g0 * 64, s * 128, bar);
            if (pair < NJOBS) tma_load_3d(sbase + OFF_RING + s * SLOT_BYTES, &tm_wl3, 0, (pair / 3) * 32, 2 * s, bar);
        }
    }
    if (warp == 13) {
        if (lane == 0) {
            for (int s = 0; s < NSLOTS; s++) {
                if (s >= 3) mbar_init(sbase + OFF_FULL + s * 8, 1);
                mbar_init(sbase + OFF_EMPTY + s * 8, 6);
            }
            mbar_init(sbase + OFF_JB2, 1);
            mbar_init(sbase + OFF_NB, 1);
            asm volatile("st.volatile.shared.u32 [%0], %1;" ::"r"(sbase + OFF_PACE), "r"(6) : "memory");
            asm volatile("fence.mbarrier_init.release.cluster;" ::: "memory");
            asm volatile("fence.proxy.async.shared::cta;" ::: "memory");
        }
        __syncwarp();
        asm volatile("bar.arrive 5, 448;" ::: "memory");
    }
    __syncwarp();
    asm volatile("barrier.cluster.arrive.relaxed.aligned;" ::: "memory");

    if (warp >= 12) {
        asm volatile("setmaxnreg.dec.sync.aligned.u32 32;");
        if (warp == 12) {
            asm volatile("bar.sync 5, 448;" ::: "memory");
            if (elect_one()) {
                const int g1 = (pair + 1) % 3, g2 = (pair + 2) % 3;
#pragma unroll 1
                for (int kc = 0; kc < 6; kc++) {
                    const uint32_t bar = sbase + OFF_FULL + (3 + kc) * 8;
                    mbar_expect_tx(bar, (kc & 1) ? SLOT_BYTES : 5 * SLOT_BYTES);
                    tma_load_5d(sbase + OFF_RING + (3 + kc) * SLOT_BYTES, &tm_p8, kc * 64, pair * 2, 0, bar);
                    if (!(kc & 1)) {
                        tma_load_2d(sbase + OFF_WOUT + g1 * WOUT_SLICE + kc * 8192, &tm_wo, rank * 192 + g1 * 64, kc * 64, bar);
                        tma_load_2d(sbase + OFF_WOUT + g2 * WOUT_SLICE + kc * 8192, &tm_wo, rank * 192 + g2 * 64, kc * 64, bar);
                    }
                }
            }
            __syncwarp();
        }
        asm volatile("barrier.cluster.wait.aligned;" ::: "memory");
        if (warp == 12) {
            if ((sbase & 0x3FFFFu) != SMEM_BASE) asm volatile("trap;");
            const uint32_t dst0 = sbase + OFF_RING + rank * 4096;
            uint32_t so = 9 * 8, ph = 1, step = 6;
            auto next_slot = [&]() {
                so += 8;
                if (so == NSLOTS * 8) { so = 0; ph ^= 1; }
            };
            unsigned mytiles = 0, seen = 0;
            auto look = [&]() {
                asm volatile("ld.relaxed.gpu.global.u32 %0, [%1];" : "=r"(seen) : "l"(&scr->prog) : "memory");
            };
            auto tile = [&](bool coarse, int coord, uint64_t pol, bool last) {
                if (rank == 0 && mytiles >= GOV_START) {
                    const unsigned need = mytiles * npair - 2 * max(GOV_TIGHT - (int)mytiles, 0);
                    unsigned spins = 0;
                    while (__any_sync(0xffffffffu, (int)(need - seen) > 0) && ++spins < 100000u) look();
                }
                mytiles++;
#pragma unroll
                for (int kc = 0; kc < 6; kc++) {
                    const uint32_t bar = sbase + OFF_FULL + so, dst = dst0 + so * (SLOT_BYTES / 8);
                    mbar_wait_bounded(sbase + OFF_EMPTY + so, ph);
                    step++;
                    if (elect_one()) {
                        mbar_expect_tx(bar, SLOT_BYTES);
                        if (coarse) tma_load_5d_mc(dst, &tm_p, kc * 64, pair * 2, coord, bar, pol);
                        else        tma_load_2d_mc(dst, &tm_c, kc * 64, coord, bar, pol);
                        asm volatile("st.volatile.shared.u32 [%0], %1;" ::"r"(sbase + OFF_PACE), "r"(step) : "memory");
                    }
                    if (kc == 0 && rank == 0 && lane == 0 && !last)
                        asm volatile("red.relaxed.gpu.global.add.u32 [%0], 1;" ::"l"(&scr->prog) : "memory");
                    next_slot();
                    if (kc == 3 && rank == 0) look();
                }
            };
#pragma unroll 1
            for (int j = 0; j < nfine; j++) {
                const uint64_t pol = j >= nfine - EF_STEPS ? POLICY_EVICT_FIRST : POLICY_EVICT_NORMAL;
                if ((j & 3) == 0 && j > 0) tile(true, j + 2 * rank, pol, false);
                tile(false, seg_row(j * npair + pair) + rank * HW, pol, j + 1 == nfine);
            }
            if (rank == 0 && lane == 0) {
                if (atomicAdd(&scr->prog, 1u) + 1 == mytiles * npair) {
                    asm volatile("st.relaxed.gpu.global.u32 [%0], 0;" ::"l"(&scr->prog) : "memory");
                    asm volatile("red.relaxed.gpu.global.add.u32 [%0], 1;" ::"l"(&scr->epoch) : "memory");
                }
            }
            __syncwarp();
            for (int s = 0; s < NSLOTS; s++) {
                mbar_wait_bounded(sbase + OFF_EMPTY + so, ph);
                next_slot();
            }
        } else if (warp == 13) {
            auto wait_pace = [&](int need) {
                unsigned spins = 0;
                while (true) {
                    uint32_t v;
                    asm volatile("ld.volatile.shared.u32 %0, [%1];" : "=r"(v) : "r"(sbase + OFF_PACE) : "memory");
                    if ((int)v >= need || ++spins > 4000000u) break;
                    __nanosleep(20);
                }
            };
            if (lane == 0) mbar_expect_tx(sbase + OFF_NB, 12 * 512);
#pragma unroll 1
            for (int k = 0; k < 12; k++) {
                const int j = k < 6 ? 2 : 3;
                wait_pace(PF_FIRST + k * 3 / 4);
                if (lane == 0)
                    tma_load_2d(sbase + OFF_SINK, &tm_cf, 0, (seg_row(j * npair + pair) + rank * HW) * 6 + (k - (j - 2) * 6) * 32,
                                sbase + OFF_NB);
            }
#pragma unroll 1
            for (int i = 5; i < nfine + nfine / 4; i++) {
                const int k5 = i / 5, t = i - k5 * 5;
                const char *b0, *b1;
                if (t == 0) {
                    b0 = (const char*)p_ptr + (size_t)((4 * k5 + 2 * rank) * npair + pair) * (16 * C * 2);
                    b1 = b0 + (size_t)npair * (16 * C * 2);
                } else {
                    b0 = (const char*)c_ptr + (size_t)(seg_row((4 * k5 + t - 1) * npair + pair) + rank * HW) * (C * 2);
                    b1 = b0 + 16 * C * 2;
                }
                wait_pace(6 * i - max(PF_LEAD0 - max(i - PF_DECAY, 0), PF_LEAD));
#pragma unroll
                for (int k = 0; k < 6; k++) {
                    asm volatile("prefetch.global.L2 [%0];" ::"l"((k < 3 ? b0 : b1) + lane * 128 + (k % 3) * 4096) : "memory");
                    __nanosleep(PF_GAP);
                }
            }
            mbar_wait_bounded(sbase + OFF_NB, 0);
        } else if (warp == 15) {
            uint32_t par, v;
            asm volatile("ld.relaxed.gpu.global.u32 %0, [%1];" : "=r"(par) : "l"(&scr->epoch) : "memory");
            uint4* clr = scr->wfrag + (~par & 1) * (6 * NFRAG * 128);
            unsigned spins = 0;
            do {
                __nanosleep(500);
                asm volatile("ld.volatile.shared.u32 %0, [%1];" : "=r"(v) : "r"(sbase + OFF_PACE) : "memory");
            } while (v < CLR_AT && ++spins < 100000u);
            for (int i = blockIdx.x * 32 + lane; i < 6 * NFRAG * 128; i += npair * 64) clr[i] = make_uint4(0u, 0u, 0u, 0u);
        }
    } else {
        uint32_t par;
        asm volatile("ld.relaxed.gpu.global.u32 %0, [%1];" : "=r"(par) : "l"(&scr->epoch) : "memory");
        asm volatile("setmaxnreg.inc.sync.aligned.u32 160;");
        asm volatile("bar.sync 5, 448;" ::: "memory");
        asm volatile("barrier.cluster.wait.aligned;" ::: "memory");
        const int wg   = warp >> 2;
        const int wtid = tid & 127;
        Ctx cx;
        cx.sbase     = sbase;
        cx.empty_tgt = mapa(sbase + OFF_EMPTY, warp & 1);
        cx.signal    = (lane == 0) && ((warp & 3) < 2);
        cx.da0       = desc_lo(sbase + OFF_WOUT + wg * WOUT_SLICE);
        const int cb = rank * 3 + wg;

        float    acc[32];
        uint32_t qp[16];
        uint32_t W[96];

        {
            uint32_t jph = 0;
            for (int job = pair; job < NJOBS; job += npair) {
                if (job % 3 == wg) {
                    if (job != pair) {
                        named_bar(wg);
                        if (wtid == 0) {
                            mbar_expect_tx(sbase + OFF_JB2, 6 * 4096);
                            for (int s = 0; s < 3; s++)
                                tma_load_3d(sbase + OFF_RING + s * SLOT_BYTES, &tm_wl3, 0, (job / 3) * 32, 2 * s, sbase + OFF_JB2);
                        }
                        for (int kc = 0; kc < 6; kc++) mbar_wait(sbase + OFF_FULL + (3 + kc) * 8, 0);
                        mbar_wait(sbase + OFF_JB2, jph);
                    }
                    float ja[16];
#define JOBK(k) wgmma_ss32<((k) > 0), (k) * 128, ((k) >> 2) * 256 + ((k) & 3) * 2>(ja, cx.da0);
                    mbar_wait(sbase + OFF_FULL, 0);
                    wg_fence();
                    JOBK(0)  JOBK(1)  JOBK(2)  JOBK(3)  JOBK(4)  JOBK(5)  JOBK(6)  JOBK(7)
                    wg_commit();
                    mbar_wait(sbase + OFF_FULL + 8, 0);
                    wg_fence();
                    JOBK(8)  JOBK(9)  JOBK(10) JOBK(11) JOBK(12) JOBK(13) JOBK(14) JOBK(15)
                    wg_commit();
                    mbar_wait(sbase + OFF_FULL + 16, 0);
                    wg_fence();
                    JOBK(16) JOBK(17) JOBK(18) JOBK(19) JOBK(20) JOBK(21) JOBK(22) JOBK(23)
#undef JOBK
                    wg_commit();
                    wg_wait<0>();
                    const int fidx = (cb * NFRAG + (job / 3) * 2) * 128 + wtid;
                    uint4* dst = scr->wfrag + (par & 1) * (6 * NFRAG * 128) + fidx;
#pragma unroll
                    for (int i = 0; i < 2; i++) {
                        asm volatile("st.relaxed.gpu.global.v4.u32 [%0], {%1, %2, %3, %4};" ::"l"(dst + i * 128),
                                     "r"(pack_neg(ja[8 * i + 0], ja[8 * i + 1])), "r"(pack_neg(ja[8 * i + 2], ja[8 * i + 3])),
                                     "r"(pack_neg(ja[8 * i + 4], ja[8 * i + 5])), "r"(pack_neg(ja[8 * i + 6], ja[8 * i + 7])) : "memory");
                    }
                }
                if (job + npair < NJOBS) asm volatile("bar.sync 4, 384;" ::: "memory");
                if (job != pair) jph ^= 1;
            }
        }

        par &= 1;
        mbar_wait(sbase + OFF_FULL, 0);
        mbar_wait(sbase + OFF_FULL + 8, 0);
        mbar_wait(sbase + OFF_FULL + 16, 0);
        asm volatile("bar.sync 6, 384;" ::: "memory");
        if (cx.signal) {
            mbar_arrive_cluster(cx.empty_tgt);
            mbar_arrive_cluster(cx.empty_tgt + 8);
            mbar_arrive_cluster(cx.empty_tgt + 16);
        }
        auto pack_q = [&]() {
            uint32_t all = 0;
#pragma unroll
            for (int i = 0; i < 16; i++) {
                qp[i] = pack_bf16(acc[2 * i], acc[2 * i + 1]);
                if (i >= 4) all |= qp[i];
            }
            qp[3] |= all & zero;
        };
        bool ready = false;
        uint32_t pu = 0;
        int turn = -1;
#define CHUNK(N, MODE) chunk<N, MODE>(acc, W, qp, zero, cx, pu, ready, turn)

        const uint4* wsrc = scr->wfrag + (par * 6 + cb) * (NFRAG * 128) + wtid;
        auto load_w = [&](int kc) {
#pragma unroll
            for (int s = 4 * kc; s < 4 * kc + 4; s++) {
                asm volatile("ld.relaxed.gpu.global.v4.u32 {%0, %1, %2, %3}, [%4];"
                             : "=r"(W[4 * s]), "=r"(W[4 * s + 1]), "=r"(W[4 * s + 2]), "=r"(W[4 * s + 3])
                             : "l"(wsrc + s * 128) : "memory");
            }
        };
        auto check_w = [&](int kc) {
            uint32_t* w = kc < 6 ? W + 16 * kc : qp;
            asm volatile(
                "{\n.reg .pred p;\n.reg .u32 m, n;\n"
                "mov.u32 n, 0;\n"
                "CHK_%=:\n"
                "mov.u32 m, %%clock;\n or.b32 m, m, 1;\n min.u32 m, m, %0;\n"
                "min.u32 m, m, %1;\n min.u32 m, m, %2;\n min.u32 m, m, %3;\n min.u32 m, m, %4;\n min.u32 m, m, %5;\n"
                "min.u32 m, m, %6;\n min.u32 m, m, %7;\n min.u32 m, m, %8;\n min.u32 m, m, %9;\n min.u32 m, m, %10;\n"
                "min.u32 m, m, %11;\n min.u32 m, m, %12;\n min.u32 m, m, %13;\n min.u32 m, m, %14;\n min.u32 m, m, %15;\n"
                "setp.ne.u32 p, m, 0;\n"
                "vote.sync.all.pred p, p, 0xffffffff;\n"
                "@p bra.uni OK_%=;\n"
                "add.u32 n, n, 1;\n"
                "setp.gt.u32 p, n, 5000000;\n"
                "@p bra.uni OK_%=;\n"
                "ld.relaxed.gpu.global.v4.u32 {%0, %1, %2, %3}, [%16];\n"
                "ld.relaxed.gpu.global.v4.u32 {%4, %5, %6, %7}, [%16 + 2048];\n"
                "ld.relaxed.gpu.global.v4.u32 {%8, %9, %10, %11}, [%16 + 4096];\n"
                "ld.relaxed.gpu.global.v4.u32 {%12, %13, %14, %15}, [%16 + 6144];\n"
                "bra.uni CHK_%=;\n"
                "OK_%=:\n}"
                : "+r"(w[0]), "+r"(w[1]), "+r"(w[2]), "+r"(w[3]), "+r"(w[4]), "+r"(w[5]), "+r"(w[6]), "+r"(w[7]),
                  "+r"(w[8]), "+r"(w[9]), "+r"(w[10]), "+r"(w[11]), "+r"(w[12]), "+r"(w[13]), "+r"(w[14]), "+r"(w[15])
                : "l"(wsrc + kc * 512) : "memory");
        };
        const uint32_t stage = sbase + OFF_WOUT + wg * WOUT_SLICE + 2 * 8192;
        const uint32_t st_addr = stage + (((lane >> 4) * 8 + (lane & 7)) << 7)
                               + (((((warp & 3) << 1) | ((lane >> 3) & 1)) ^ (lane & 7)) << 4);
        auto publish = [&](int s) {
            if (pair == (NJOBS + s) % npair) {
                uint32_t a[4];
                asm volatile("ldmatrix.sync.aligned.m8n8.x4.trans.shared.b16 {%0, %1, %2, %3}, [%4];"
                             : "=r"(a[0]), "=r"(a[1]), "=r"(a[2]), "=r"(a[3]) : "r"(st_addr + s * 8192) : "memory");
                asm volatile("st.relaxed.gpu.global.v4.u32 [%0], {%1, %2, %3, %4};" ::"l"(wsrc + (24 + s) * 128),
                             "r"(enc_neg(a[0])), "r"(enc_neg(a[1])), "r"(enc_neg(a[2])), "r"(enc_neg(a[3])) : "memory");
            }
        };
        CHUNK(0, COARSE);
        CHUNK(1, COARSE);
        CHUNK(2, COARSE);
        publish(0);
        load_w(0);
        CHUNK(3, COARSE);
        publish(1);
        load_w(1);
        CHUNK(4, COARSE);
        publish(2);
        load_w(2);
        CHUNK(5, COARSE);
        publish(3);
        wg_wait<0>();
        release<5>(cx);
        pack_q();

        auto flush_part = [&](int row, int part) {
            if (part == 0) {
                asm volatile("fence.proxy.async.shared::cta;" ::: "memory");
                named_bar(wg);
            }
            if (wtid == 0) {
                tma_store_2d(&tm_out, cb * 64, row + (part >> 1) * HW + (part & 1) * 16, stage + part * 8192, POLICY_EVICT_FIRST);
                if (part == 3) asm volatile("cp.async.bulk.commit_group;" ::: "memory");
            }
        };
        auto init_acc = [&](int t) {
#pragma unroll
            for (int b = 0; b < 2; b++) {
#pragma unroll
                for (int h = 0; h < 2; h++) {
                    const uint32_t q = qp[t * 4 + b * 2 + h];
                    const float lo = __uint_as_float(q << 16), hi = __uint_as_float(q & 0xffff0000u);
#pragma unroll
                    for (int dy = 0; dy < 2; dy++) {
                        acc[16 * dy + 8 * b + 2 * h]         = dy ? dup(lo, one) : lo;
                        acc[16 * dy + 8 * b + 2 * h + 1]     = dup(lo, one);
                        acc[16 * dy + 8 * b + 4 + 2 * h]     = dy ? dup(hi, one) : hi;
                        acc[16 * dy + 8 * b + 4 + 2 * h + 1] = dup(hi, one);
                    }
                }
            }
        };
        auto stage_tile = [&](int slot) {
            if (wtid == 0) asm volatile("cp.async.bulk.wait_group.read 0;" ::: "memory");
            named_bar(wg);
            wg_wait<0>();
            if (cx.signal) mbar_arrive_cluster(cx.empty_tgt + slot * 8);
#pragma unroll
            for (int i = 0; i < 8; i += 2) {
                stsm_x4_t(st_addr + i * 4096,
                          pack_bf16(acc[4 * i + 0], acc[4 * i + 1]), pack_bf16(acc[4 * i + 2], acc[4 * i + 3]),
                          pack_bf16(acc[4 * i + 4], acc[4 * i + 5]), pack_bf16(acc[4 * i + 6], acc[4 * i + 7]));
            }
        };

        auto load_wo = [&]() {
#pragma unroll
            for (int s = 0; s < 4; s++) {
                asm volatile("ld.global.ca.v4.u32 {%0, %1, %2, %3}, [%4];"
                             : "=r"(qp[4 * s]), "=r"(qp[4 * s + 1]), "=r"(qp[4 * s + 2]), "=r"(qp[4 * s + 3])
                             : "l"(wsrc + (24 + s) * 128) : "memory");
            }
        };

        init_acc(0);
        check_w(0);
        load_w(3);
        load_w(4);
        CHUNK(6, FINE);
        check_w(1);
        CHUNK(7, FINE);
        check_w(2);
        CHUNK(8, FINE);
        check_w(3);
        load_w(5);
        CHUNK(9, FINE);
        check_w(4);
        CHUNK(10, FINE);
        check_w(5);
        CHUNK(11, FINE);

        int seg = pair;
        int prow = seg_row(seg);
        while (true) {
            stage_tile(slot_of<11>());
            init_acc(1);
            CHUNK(12, FINE);
            flush_part(prow, 0);
            CHUNK(13, FINE);
            CHUNK(14, FINE);
            flush_part(prow, 1);
            CHUNK(15, FINE);
            flush_part(prow, 2);
            CHUNK(16, FINE);
            flush_part(prow, 3);
            CHUNK(17, FINE);
            seg += npair;
            prow = seg_row(seg);
            stage_tile(slot_of<17>());
            init_acc(2);
            CHUNK(18, FINE);
            flush_part(prow, 0);
            CHUNK(19, FINE);
            CHUNK(20, FINE);
            flush_part(prow, 1);
            CHUNK(21, FINE);
            flush_part(prow, 2);
            CHUNK(22, FINE);
            flush_part(prow, 3);
            CHUNK(23, FINE);
            seg += npair;
            prow = seg_row(seg);
            stage_tile(slot_of<23>());
            init_acc(3);
            CHUNK(24, FINE);
            flush_part(prow, 0);
            CHUNK(25, FINE);
            load_wo();
            CHUNK(26, FINE);
            flush_part(prow, 1);
            CHUNK(27, FINE);
            flush_part(prow, 2);
            CHUNK(28, FINE);
            flush_part(prow, 3);
            CHUNK(29, FINE);
            seg += npair;
            prow = seg_row(seg);
            if (seg + npair >= NSEG) break;
            if (seg >= NSEG - (4 * SKEW_UNITS + 1) * npair) turn = wg;
            stage_tile(slot_of<29>());
            CHUNK(30, COARSE);
            flush_part(prow, 0);
            CHUNK(31, COARSE);
            check_w(6);
            CHUNK(32, COARSE_REG);
            CHUNK(33, COARSE_REG);
            flush_part(prow, 1);
            CHUNK(34, COARSE_REG);
            CHUNK(35, COARSE_REG);
            wg_wait<0>();
            release<35>(cx);
            pack_q();
            init_acc(0);
            CHUNK(36, FINE);
            flush_part(prow, 2);
            CHUNK(37, FINE);
            CHUNK(38, FINE);
            CHUNK(39, FINE);
            flush_part(prow, 3);
            CHUNK(40, FINE);
            CHUNK(41, FINE);
            seg += npair;
            prow = seg_row(seg);
            pu ^= 1;
        }
#undef CHUNK
        stage_tile(slot_of<29>());
#pragma unroll
        for (int part = 0; part < 4; part++) flush_part(prow, part);
        if (wtid == 0) asm volatile("cp.async.bulk.wait_group.read 0;" ::: "memory");
    }
}

typedef CUresult (*EncodeFn)(CUtensorMap*, CUtensorMapDataType, cuuint32_t, void*, const cuuint64_t*, const cuuint64_t*,
                             const cuuint32_t*, const cuuint32_t*, CUtensorMapInterleave, CUtensorMapSwizzle,
                             CUtensorMapL2promotion, CUtensorMapFloatOOBfill);

void encode(EncodeFn fn, CUtensorMap* tm, const void* ptr, int rank, const cuuint64_t* dims, const cuuint64_t* strides,
            const cuuint32_t* box, CUtensorMapSwizzle swizzle = CU_TENSOR_MAP_SWIZZLE_128B,
            CUtensorMapL2promotion promotion = CU_TENSOR_MAP_L2_PROMOTION_NONE) {
    const cuuint32_t es[5] = {1, 1, 1, 1, 1};
    fn(tm, CU_TENSOR_MAP_DATA_TYPE_BFLOAT16, (cuuint32_t)rank, const_cast<void*>(ptr), dims, strides, box, es,
       CU_TENSOR_MAP_INTERLEAVE_NONE, swizzle, promotion, CU_TENSOR_MAP_FLOAT_OOB_FILL_NONE);
}

}

extern "C" void kernel_launch(void* const* d_in, const int* in_sizes, int n_in, void* d_out, int out_size) {
    (void)in_sizes; (void)n_in; (void)out_size;
    const __nv_bfloat16* c_fine   = (const __nv_bfloat16*)d_in[0];
    const __nv_bfloat16* p_coarse = (const __nv_bfloat16*)d_in[1];
    const __nv_bfloat16* w_lat    = (const __nv_bfloat16*)d_in[2];
    const __nv_bfloat16* w_out    = (const __nv_bfloat16*)d_in[3];

    static EncodeFn fn = nullptr;
    static int np = 0;
    static Scratch* scr = nullptr;
    if (!fn) {
        void* p = nullptr;
        cudaDriverEntryPointQueryResult qr;
        cudaGetDriverEntryPoint("cuTensorMapEncodeTiled", &p, cudaEnableDefault, &qr);
        fn = (EncodeFn)p;
        cudaGetSymbolAddress((void**)&scr, g_scratch);
        cudaFuncSetAttribute(fpn_kernel<NPAIRS>, cudaFuncAttributeMaxDynamicSharedMemorySize, SMEM_BYTES);
        cudaFuncSetAttribute(fpn_kernel<0>, cudaFuncAttributeMaxDynamicSharedMemorySize, SMEM_BYTES);
        cudaLaunchConfig_t cfg = {};
        cfg.gridDim = dim3(2); cfg.blockDim = dim3(NTHREADS); cfg.dynamicSmemBytes = SMEM_BYTES;
        cudaLaunchAttribute at[1];
        at[0].id = cudaLaunchAttributeClusterDimension;
        at[0].val.clusterDim.x = 2; at[0].val.clusterDim.y = 1; at[0].val.clusterDim.z = 1;
        cfg.attrs = at; cfg.numAttrs = 1;
        if (cudaOccupancyMaxActiveClusters(&np, fpn_kernel<0>, &cfg) != cudaSuccess || np < 1) np = 1;
        if (np > NPAIRS) np = NPAIRS;
        while ((NSEG / 4) % np) np--;
    }

    CUtensorMap tm_cf, tm_c, tm_p, tm_wl3, tm_out, tm_p8, tm_wo;
    {
        const cuuint64_t dims[2] = {(cuuint64_t)C, (cuuint64_t)NPIX};
        const cuuint64_t str[1]  = {(cuuint64_t)C * 2};
        const cuuint32_t box_in[2]  = {64, 32};
        const cuuint32_t box_out[2] = {64, 16};
        encode(fn, &tm_c, c_fine, 2, dims, str, box_in);
        encode(fn, &tm_out, d_out, 2, dims, str, box_out);
    }
    {
        const cuuint64_t dims[5] = {(cuuint64_t)C, 2, 4, (cuuint64_t)(2 * np), (cuuint64_t)(NSEG / np)};
        const cuuint64_t str[4]  = {(cuuint64_t)4 * C * 2, (cuuint64_t)C * 2, (cuuint64_t)8 * C * 2, (cuuint64_t)np * 16 * C * 2};
        const cuuint32_t box[5]  = {64, 2, 4, 2, 2};
        encode(fn, &tm_p, p_coarse, 5, dims, str, box);
        const cuuint32_t box8[5] = {64, 2, 4, 2, 4};
        encode(fn, &tm_p8, p_coarse, 5, dims, str, box8);
    }
    {
        const cuuint64_t dims[2] = {(cuuint64_t)C, (cuuint64_t)C};
        const cuuint64_t str[1]  = {(cuuint64_t)C * 2};
        const cuuint32_t box[2] = {64, 128};
        encode(fn, &tm_wo, w_out, 2, dims, str, box);
    }
    {
        const cuuint64_t dims[3] = {64, (cuuint64_t)C, 6};
        const cuuint64_t str[2]  = {(cuuint64_t)C * 2, 128};
        const cuuint32_t box[3]  = {64, 32, 2};
        encode(fn, &tm_wl3, w_lat, 3, dims, str, box);
    }
    {
        const cuuint64_t dims[2] = {64, (cuuint64_t)NPIX * 6};
        const cuuint64_t str[1]  = {128};
        const cuuint32_t box[2]  = {8, 32};
        encode(fn, &tm_cf, c_fine, 2, dims, str, box, CU_TENSOR_MAP_SWIZZLE_NONE, CU_TENSOR_MAP_L2_PROMOTION_L2_128B);
    }
    auto kernel = np == NPAIRS ? fpn_kernel<NPAIRS> : fpn_kernel<0>;
    kernel<<<2 * np, NTHREADS, SMEM_BYTES>>>(scr, c_fine, p_coarse, NSEG / np, 1.0f, 0u,
                                             tm_wo, tm_wl3, tm_p8, tm_c, tm_p, tm_out, tm_cf);
}
```

```cpp
#include <cuda_runtime.h>
#include <cuda_bf16.h>
#include <cuda.h>
#include <stdint.h>

namespace {

constexpr int C          = 384;
constexpr int HW         = 384;
constexpr int NPIX       = HW * HW;
constexpr int NSEG       = NPIX / 64;
constexpr int NJOBS      = 36;

constexpr int NFRAG      = 28;
constexpr int NSLOTS     = 10;
constexpr int NPAIRS     = 64;
constexpr int PF_LEAD    = 5;
constexpr int PF_LEAD0   = 18;
constexpr int PF_DECAY   = 12;
constexpr int PF_FIRST   = 11;
constexpr int PF_GAP     = 50;
constexpr int GOV_START  = 12;
constexpr int GOV_TIGHT  = 26;
constexpr int EF_TILES   = 11;
constexpr int SKEW_TILES = 4;
constexpr int SCHED      = 4332367;
constexpr int CLR_AT     = 20;

constexpr int SLOT_BYTES  = 8192;
constexpr int WOUT_SLICE  = 384 * 128;
constexpr int OFF_WOUT    = 0;
constexpr int OFF_RING    = 3 * WOUT_SLICE;
constexpr int OFF_FULL    = OFF_RING + NSLOTS * SLOT_BYTES;
constexpr int OFF_EMPTY   = OFF_FULL + 8 * NSLOTS;
constexpr int OFF_JB2     = OFF_EMPTY + 8 * NSLOTS;
constexpr int OFF_PACE    = OFF_JB2 + 8;
constexpr int OFF_NB      = OFF_PACE + 8;
constexpr int OFF_SINK    = (OFF_NB + 8 + 127) / 128 * 128;
constexpr int SMEM_BYTES  = OFF_SINK + 512;
static_assert(SMEM_BYTES <= 232448, "smem");
static_assert(NSLOTS == 10, "a unit (30 ring items) must be an odd number of rounds of the ring");

constexpr int      SMEM_BASE = 1024;
constexpr uint64_t DESC_RING = 0x4000004000010000ull + ((SMEM_BASE + OFF_RING) >> 4);

constexpr int NTHREADS = 512;
constexpr uint64_t POLICY_EVICT_FIRST  = 0x12F0000000000000ull;
constexpr uint64_t POLICY_EVICT_NORMAL = 0x1000000000000000ull;

struct Scratch {
    uint4    wfrag[2 * 6 * NFRAG * 128];
    unsigned epoch;
    unsigned pad0[31];
    unsigned prog;
};
__device__ Scratch g_scratch;

__device__ __forceinline__ uint32_t smem_u32(const void* p) { return (uint32_t)__cvta_generic_to_shared(p); }

__device__ __forceinline__ void mbar_init(uint32_t bar, uint32_t cnt) {
    asm volatile("mbarrier.init.shared::cta.b64 [%0], %1;" ::"r"(bar), "r"(cnt) : "memory");
}
__device__ __forceinline__ void mbar_expect_tx(uint32_t bar, uint32_t bytes) {
    asm volatile("mbarrier.arrive.expect_tx.shared::cta.b64 _, [%0], %1;" ::"r"(bar), "r"(bytes) : "memory");
}
__device__ __forceinline__ void mbar_wait_bounded(uint32_t bar, uint32_t parity) {
    asm volatile(
        "{\n"
        ".reg .pred p;\n"
        ".reg .u32 n;\n"
        "mbarrier.try_wait.parity.shared::cta.b64 p, [%0], %1;\n"
        "@p bra DONE_%=;\n"
        "mov.u32 n, 0;\n"
        "WAIT_%=:\n"
        "mbarrier.try_wait.parity.shared::cta.b64 p, [%0], %1;\n"
        "@p bra DONE_%=;\n"
        "add.u32 n, n, 1;\n"
        "setp.lt.u32 p, n, 4000000;\n"
        "@p bra WAIT_%=;\n"
        "trap;\n"
        "DONE_%=:\n"
        "}\n" ::"r"(bar), "r"(parity) : "memory");
}
__device__ __forceinline__ void mbar_wait(uint32_t bar, uint32_t parity) {
    asm volatile(
        "{\n"
        ".reg .pred p;\n"
        "WAIT_%=:\n"
        "mbarrier.try_wait.parity.shared::cta.b64 p, [%0], %1;\n"
        "@!p bra WAIT_%=;\n"
        "}\n" ::"r"(bar), "r"(parity) : "memory");
}
__device__ __forceinline__ bool mbar_try(uint32_t bar, uint32_t parity) {
    uint32_t r;
    asm volatile("{\n.reg .pred p;\nmbarrier.test_wait.parity.shared::cta.b64 p, [%1], %2;\nselp.u32 %0, 1, 0, p;\n}\n"
                 : "=r"(r) : "r"(bar), "r"(parity) : "memory");
    return r != 0;
}
__device__ __forceinline__ void mbar_arrive_cluster(uint32_t cluster_addr) {
    asm volatile("mbarrier.arrive.shared::cluster.b64 _, [%0];" ::"r"(cluster_addr) : "memory");
}
__device__ __forceinline__ uint32_t mapa(uint32_t addr, uint32_t rank) {
    uint32_t r;
    asm("mapa.shared::cluster.u32 %0, %1, %2;" : "=r"(r) : "r"(addr), "r"(rank));
    return r;
}
__device__ __forceinline__ void named_bar(int wg) {
    asm volatile("bar.sync %0, 128;" ::"r"(wg + 1) : "memory");
}

__device__ __forceinline__ void tma_load_2d(uint32_t dst, const CUtensorMap* tm, int c0, int c1, uint32_t bar) {
    asm volatile("cp.async.bulk.tensor.2d.shared::cluster.global.mbarrier::complete_tx::bytes [%0], [%1, {%2, %3}], [%4];"
                 ::"r"(dst), "l"(tm), "r"(c0), "r"(c1), "r"(bar) : "memory");
}
__device__ __forceinline__ void tma_load_3d(uint32_t dst, const CUtensorMap* tm, int c0, int c1, int c2, uint32_t bar) {
    asm volatile("cp.async.bulk.tensor.3d.shared::cluster.global.mbarrier::complete_tx::bytes [%0], [%1, {%2, %3, %4}], [%5];"
                 ::"r"(dst), "l"(tm), "r"(c0), "r"(c1), "r"(c2), "r"(bar) : "memory");
}
__device__ __forceinline__ void tma_load_5d(uint32_t dst, const CUtensorMap* tm, int c0, int c3, int c4, uint32_t bar) {
    asm volatile("cp.async.bulk.tensor.5d.shared::cluster.global.mbarrier::complete_tx::bytes [%0], [%1, {%2, 0, 0, %3, %4}], [%5];"
                 ::"r"(dst), "l"(tm), "r"(c0), "r"(c3), "r"(c4), "r"(bar) : "memory");
}
__device__ __forceinline__ void tma_load_2d_mc(uint32_t dst, const CUtensorMap* tm, int c0, int c1, uint32_t bar, uint64_t pol) {
    asm volatile("cp.async.bulk.tensor.2d.shared::cluster.global.mbarrier::complete_tx::bytes.multicast::cluster.L2::cache_hint"
                 " [%0], [%1, {%2, %3}], [%4], %5, %6;"
                 ::"r"(dst), "l"(tm), "r"(c0), "r"(c1), "r"(bar), "h"((uint16_t)3), "l"(pol) : "memory");
}
__device__ __forceinline__ void tma_load_5d_mc(uint32_t dst, const CUtensorMap* tm, int c0, int c3, int c4, uint32_t bar, uint64_t pol) {
    asm volatile("cp.async.bulk.tensor.5d.shared::cluster.global.mbarrier::complete_tx::bytes.multicast::cluster.L2::cache_hint"
                 " [%0], [%1, {%2, 0, 0, %3, %4}], [%5], %6, %7;"
                 ::"r"(dst), "l"(tm), "r"(c0), "r"(c3), "r"(c4), "r"(bar), "h"((uint16_t)3), "l"(pol) : "memory");
}
__device__ __forceinline__ void tma_store_2d(const CUtensorMap* tm, int c0, int c1, uint32_t src, uint64_t pol) {
    asm volatile("cp.async.bulk.tensor.2d.global.shared::cta.bulk_group.L2::cache_hint [%0, {%1, %2}], [%3], %4;"
                 ::"l"(tm), "r"(c0), "r"(c1), "r"(src), "l"(pol) : "memory");
}
__device__ __forceinline__ bool elect_one() {
    uint32_t r;
    asm volatile("{\n.reg .pred p;\nelect.sync _|p, 0xffffffff;\nselp.u32 %0, 1, 0, p;\n}" : "=r"(r));
    return r != 0;
}
__device__ __forceinline__ void prefetch_tmap(const CUtensorMap* tm) {
    asm volatile("prefetch.tensormap [%0];" ::"l"(tm) : "memory");
}

__device__ __forceinline__ void wg_fence()  { asm volatile("wgmma.fence.sync.aligned;" ::: "memory"); }
__device__ __forceinline__ void wg_commit() { asm volatile("wgmma.commit_group.sync.aligned;" ::: "memory"); }
template <int N> __device__ __forceinline__ void wg_wait() { asm volatile("wgmma.wait_group.sync.aligned %0;" ::"n"(N) : "memory"); }

#define ACC16(a)                                                                                              \
    "+f"(a[0]), "+f"(a[1]), "+f"(a[2]), "+f"(a[3]), "+f"(a[4]), "+f"(a[5]), "+f"(a[6]), "+f"(a[7]),           \
    "+f"(a[8]), "+f"(a[9]), "+f"(a[10]), "+f"(a[11]), "+f"(a[12]), "+f"(a[13]), "+f"(a[14]), "+f"(a[15])
#define ACC32(a)                                                                                              \
    ACC16(a),                                                                                                 \
    "+f"(a[16]), "+f"(a[17]), "+f"(a[18]), "+f"(a[19]), "+f"(a[20]), "+f"(a[21]), "+f"(a[22]), "+f"(a[23]),   \
    "+f"(a[24]), "+f"(a[25]), "+f"(a[26]), "+f"(a[27]), "+f"(a[28]), "+f"(a[29]), "+f"(a[30]), "+f"(a[31])
#define ACC16_STR "{%0, %1, %2, %3, %4, %5, %6, %7, %8, %9, %10, %11, %12, %13, %14, %15}"
#define ACC32_STR                                                                                             \
    "{%0, %1, %2, %3, %4, %5, %6, %7, %8, %9, %10, %11, %12, %13, %14, %15, "                                 \
    "%16, %17, %18, %19, %20, %21, %22, %23, %24, %25, %26, %27, %28, %29, %30, %31}"

template <int BOFF>
__device__ __forceinline__ void wgmma_rs(float (&d)[32], uint32_t a0, uint32_t a1, uint32_t a2, uint32_t a3) {
    asm volatile("{\n.reg .b64 db;\n"
                 "mov.b64 db, %36;\n"
                 "wgmma.mma_async.sync.aligned.m64n64k16.f32.bf16.bf16 " ACC32_STR
                 ", {%32, %33, %34, %35}, db, 1, -1, 1, 0;\n}"
                 : ACC32(d) : "r"(a0), "r"(a1), "r"(a2), "r"(a3), "n"(DESC_RING + BOFF));
}
template <int ACCUM, int AOFF, int BOFF>
__device__ __forceinline__ void wgmma_ss(float (&d)[32], uint32_t da_lo) {
    asm volatile("{\n.reg .b64 da, db;\n.reg .b32 lo;\n"
                 "add.u32 lo, %32, %34;\nmov.b64 da, {lo, 0x40000040};\n"
                 "mov.b64 db, %35;\n"
                 "wgmma.mma_async.sync.aligned.m64n64k16.f32.bf16.bf16 " ACC32_STR
                 ", da, db, %33, 1, 1, 1, 0;\n}"
                 : ACC32(d) : "r"(da_lo), "n"(ACCUM), "n"(AOFF), "n"(DESC_RING + BOFF));
}
template <int ACCUM, int AOFF, int BOFF>
__device__ __forceinline__ void wgmma_ss32(float (&d)[16], uint32_t da_lo) {
    asm volatile("{\n.reg .b64 da, db;\n.reg .b32 lo;\n"
                 "add.u32 lo, %16, %18;\nmov.b64 da, {lo, 0x40000040};\n"
                 "mov.b64 db, %19;\n"
                 "wgmma.mma_async.sync.aligned.m64n32k16.f32.bf16.bf16 " ACC16_STR
                 ", da, db, %17, 1, 1, 1, 0;\n}"
                 : ACC16(d) : "r"(da_lo), "n"(ACCUM), "n"(AOFF), "n"(DESC_RING + BOFF));
}
__device__ __forceinline__ uint32_t desc_lo(uint32_t addr) { return ((addr & 0x3FFFFu) >> 4) | (1u << 16); }
__device__ __forceinline__ uint32_t pack_bf16(float lo, float hi) {
    uint32_t r;
    asm("cvt.rn.bf16x2.f32 %0, %1, %2;" : "=r"(r) : "f"(hi), "f"(lo));
    return r;
}
__device__ __forceinline__ uint32_t enc_neg(uint32_t pair) {
    const uint32_t v = pair ^ 0x80008000u;
    return v == 0u ? 0x80008000u : v;
}
__device__ __forceinline__ uint32_t pack_neg(float lo, float hi) { return enc_neg(pack_bf16(lo, hi)); }
__device__ __forceinline__ float dup(float x, float one) {
    float r;
    asm volatile("mul.f32 %0, %1, %2;" : "=f"(r) : "f"(x), "f"(one));
    return r;
}
__device__ __forceinline__ void stsm_x4_t(uint32_t addr, uint32_t r0, uint32_t r1, uint32_t r2, uint32_t r3) {
    asm volatile("stmatrix.sync.aligned.m8n8.x4.trans.shared.b16 [%0], {%1, %2, %3, %4};"
                 ::"r"(addr), "r"(r0), "r"(r1), "r"(r2), "r"(r3) : "memory");
}

struct Ctx {
    uint32_t sbase;
    uint32_t da0;
    uint32_t empty_tgt;
    bool     signal;
};

template <int N> __device__ __forceinline__ constexpr uint32_t slot_of() { return (3 + N) % NSLOTS; }
template <int N> __device__ __forceinline__ uint32_t phase_of(uint32_t pu) { return pu ^ (((3 + N) / NSLOTS) & 1); }
template <int N> __device__ __forceinline__ void release(const Ctx& cx) {
    if (cx.signal) mbar_arrive_cluster(cx.empty_tgt + slot_of<N>() * 8);
}

enum { FINE, COARSE, COARSE_REG };
template <int N, int MODE, bool SKEW>
__device__ __forceinline__ void chunk(float (&acc)[32], const uint32_t (&W)[96], const uint32_t (&A)[16], uint32_t zero,
                                      const Ctx& cx, uint32_t pu, bool& ready, int wg) {
    constexpr int KC = N % 6;
    constexpr int B  = slot_of<N>() * 512;
    if (!ready) mbar_wait(cx.sbase + OFF_FULL + slot_of<N>() * 8, phase_of<N>(pu));
    ready = mbar_try(cx.sbase + OFF_FULL + slot_of<N + 1>() * 8, phase_of<N + 1>(pu));
    if (SKEW) {
        const int id = 8 + ((N / 6) & 1) * 4 + wg;
        if (KC == 2 && wg > 0) asm volatile("bar.sync %0, 256;" ::"r"(id - 1) : "memory");
        if (KC == 4 && wg < 2) asm volatile("bar.arrive %0, 256;" ::"r"(id) : "memory");
    }
    if (MODE == FINE) {
        wg_fence();
        wgmma_rs<B + 0>(acc, W[KC * 16 + 0],  W[KC * 16 + 1],  W[KC * 16 + 2],  W[KC * 16 + 3]);
        wgmma_rs<B + 2>(acc, W[KC * 16 + 4],  W[KC * 16 + 5],  W[KC * 16 + 6],  W[KC * 16 + 7]);
        wgmma_rs<B + 4>(acc, W[KC * 16 + 8],  W[KC * 16 + 9],  W[KC * 16 + 10], W[KC * 16 + 11]);
        wgmma_rs<B + 6>(acc, W[KC * 16 + 12], W[KC * 16 + 13], W[KC * 16 + 14], W[KC * 16 + 15]);
    } else {
        if (MODE == COARSE) {
            wg_fence();
            wgmma_ss<(KC > 0), KC * 4 * 128, B>(acc, cx.da0);
        } else {
            uint32_t a[4];
            asm volatile("{\n.reg .u32 z;\nmov.u32 z, %%clock;\nand.b32 z, z, %8;\n"
                         "xor.b32 %0, %4, z;\nxor.b32 %1, %5, z;\nxor.b32 %2, %6, z;\nxor.b32 %3, %7, z;\n}"
                         : "=r"(a[0]), "=r"(a[1]), "=r"(a[2]), "=r"(a[3])
                         : "r"(A[((KC + 2) & 3) * 4]), "r"(A[((KC + 2) & 3) * 4 + 1]), "r"(A[((KC + 2) & 3) * 4 + 2]),
                           "r"(A[((KC + 2) & 3) * 4 + 3]), "r"(zero));
            wg_fence();
            wgmma_rs<B>(acc, a[0], a[1], a[2], a[3]);
            wg_commit();
        }
        wgmma_ss<1, (KC * 4 + 1) * 128, B + 2>(acc, cx.da0);
        wgmma_ss<1, (KC * 4 + 2) * 128, B + 4>(acc, cx.da0);
        wgmma_ss<1, (KC * 4 + 3) * 128, B + 6>(acc, cx.da0);
    }
    wg_commit();
    if (KC > 0) {
        wg_wait<1>();
        release<N - (KC > 0)>(cx);
    }
}

__host__ __device__ constexpr int sched_n(int t) { int v = SCHED; for (int i = t; i < 7; i++) v /= 10; return v % 10; }
__host__ __device__ constexpr int sched_pos(int n, int k) { return n == 4 ? (k ? k + 1 : 0) : n == 5 ? k : k * 6 / n; }
__host__ __device__ constexpr int sched_sent(int t, int pos) {
    int c = 0;
    for (int i = 1; i < t; i++) c += sched_n(i);
    for (int k = 0; t >= 1 && t <= 7 && k < sched_n(t); k++) c += sched_pos(sched_n(t), k) < pos;
    return c;
}
__host__ __device__ constexpr bool sched_ok() {
    for (int t = 1; t <= 7; t++) if (sched_sent(t + 1, 0) > 4 * t) return false;
    return sched_sent(6, 0) >= 8;
}
static_assert(sched_ok(), "a piece is sent after its tile has been staged; tiles 0 and 1 are gone when tile 6 starts");
__host__ __device__ constexpr int piece_off(int m) {
    const int i = m % 24, block = i >= 20 ? 8 + 4 * (i - 20) : i < 8 ? i : 9 + (i - 8) / 3 * 4 + (i - 8) % 3;
    return block * 2048;
}
template <int V> struct IC { static constexpr int v = V; };

__device__ __forceinline__ int seg_row(int g) {
    const int y = g / 12;
    return y * (2 * HW) + (g - y * 12) * 32;
}

__device__ __forceinline__ bool tile_of(int i, int nfine, int& j) {
    int u = i / 5, t = i - u * 5;
    const int e = i - (nfine + nfine / 4 - 10);
    if (e >= 0) { u = nfine / 4 - 2 + (e == 0); t = max(e - 1, 0); }
    j = 4 * u + max(t - 1, 0);
    return t == 0;
}

template <int NP>
__global__ void __cluster_dims__(2, 1, 1) __launch_bounds__(NTHREADS, 1)
fpn_kernel(Scratch* scr, const __nv_bfloat16* __restrict__ c_ptr, const __nv_bfloat16* __restrict__ p_ptr,
           const int nsteps, const float one, const uint32_t zero,
           const __grid_constant__ CUtensorMap tm_wo, const __grid_constant__ CUtensorMap tm_wl3,
           const __grid_constant__ CUtensorMap tm_p8, const __grid_constant__ CUtensorMap tm_c,
           const __grid_constant__ CUtensorMap tm_p, const __grid_constant__ CUtensorMap tm_out,
           const __grid_constant__ CUtensorMap tm_cf)
{
    extern __shared__ __align__(1024) uint8_t smem[];
    const uint32_t sbase = smem_u32(smem);
    const int tid   = threadIdx.x;
    const int warp  = __shfl_sync(0xffffffffu, tid >> 5, 0);
    const int lane  = tid & 31;
    const int rank  = blockIdx.x & 1;
    const int pair  = blockIdx.x >> 1;
    const int npair = NP ? NP : gridDim.x >> 1;
    const int nfine = NP ? NSEG / (NP ? NP : 1) : nsteps;

    if (tid == 480) {
        prefetch_tmap(&tm_wo); prefetch_tmap(&tm_wl3); prefetch_tmap(&tm_p8);
        prefetch_tmap(&tm_c); prefetch_tmap(&tm_p); prefetch_tmap(&tm_out); prefetch_tmap(&tm_cf);
    }
    if (warp == 12 && elect_one()) {
        for (int s = 0; s < 3; s++) mbar_init(sbase + OFF_FULL + s * 8, 1);
        asm volatile("fence.mbarrier_init.release.cluster;" ::: "memory");
        asm volatile("fence.proxy.async.shared::cta;" ::: "memory");
        const int g0 = pair % 3;
#pragma unroll 1
        for (int s = 0; s < 3; s++) {
            const uint32_t bar = sbase + OFF_FULL + s * 8;
            const uint32_t dst = sbase + OFF_WOUT + g0 * WOUT_SLICE + s * 16384;
            mbar_expect_tx(bar, pair < NJOBS ? 3 * SLOT_BYTES : 2 * SLOT_BYTES);
            tma_load_2d(dst, &tm_wo, rank * 192 + g0 * 64, s * 128, bar);
            if (pair < NJOBS) tma_load_3d(sbase + OFF_RING + s * SLOT_BYTES, &tm_wl3, 0, (pair / 3) * 32, 2 * s, bar);
        }
    }
    if (warp == 13) {
        if (lane == 0) {
            for (int s = 0; s < NSLOTS; s++) {
                if (s >= 3) mbar_init(sbase + OFF_FULL + s * 8, 1);
                mbar_init(sbase + OFF_EMPTY + s * 8, 6);
            }
            mbar_init(sbase + OFF_JB2, 1);
            mbar_init(sbase + OFF_NB, 1);
            asm volatile("st.volatile.shared.u32 [%0], %1;" ::"r"(sbase + OFF_PACE), "r"(6) : "memory");
            asm volatile("fence.mbarrier_init.release.cluster;" ::: "memory");
            asm volatile("fence.proxy.async.shared::cta;" ::: "memory");
        }
        __syncwarp();
        asm volatile("bar.arrive 5, 448;" ::: "memory");
    }
    __syncwarp();
    asm volatile("barrier.cluster.arrive.relaxed.aligned;" ::: "memory");

    if (warp < 12) {
        uint32_t par;
        asm volatile("ld.relaxed.gpu.global.u32 %0, [%1];" : "=r"(par) : "l"(&scr->epoch) : "memory");
        asm volatile("setmaxnreg.inc.sync.aligned.u32 160;");
        asm volatile("bar.sync 5, 448;" ::: "memory");
        asm volatile("barrier.cluster.wait.aligned;" ::: "memory");
        const int wg   = warp >> 2;
        const int wtid = tid & 127;
        Ctx cx;
        cx.sbase     = sbase;
        cx.empty_tgt = mapa(sbase + OFF_EMPTY, warp & 1);
        cx.signal    = (lane == 0) && ((warp & 3) < 2);
        cx.da0       = desc_lo(sbase + OFF_WOUT + wg * WOUT_SLICE);
        const int cb = rank * 3 + wg;

        float    acc[32];
        uint32_t qp[16];
        uint32_t W[96];

        {
            uint32_t jph = 0;
            for (int job = pair; job < NJOBS; job += npair) {
                if (job % 3 == wg) {
                    if (job != pair) {
                        named_bar(wg);
                        if (wtid == 0) {
                            mbar_expect_tx(sbase + OFF_JB2, 6 * 4096);
                            for (int s = 0; s < 3; s++)
                                tma_load_3d(sbase + OFF_RING + s * SLOT_BYTES, &tm_wl3, 0, (job / 3) * 32, 2 * s, sbase + OFF_JB2);
                        }
                        for (int kc = 0; kc < 6; kc++) mbar_wait(sbase + OFF_FULL + (3 + kc) * 8, 0);
                        mbar_wait(sbase + OFF_JB2, jph);
                    }
                    float ja[16];
#define JOBK(k) wgmma_ss32<((k) > 0), (k) * 128, ((k) >> 2) * 256 + ((k) & 3) * 2>(ja, cx.da0);
                    mbar_wait(sbase + OFF_FULL, 0);
                    wg_fence();
                    JOBK(0)  JOBK(1)  JOBK(2)  JOBK(3)  JOBK(4)  JOBK(5)  JOBK(6)  JOBK(7)
                    wg_commit();
                    mbar_wait(sbase + OFF_FULL + 8, 0);
                    wg_fence();
                    JOBK(8)  JOBK(9)  JOBK(10) JOBK(11) JOBK(12) JOBK(13) JOBK(14) JOBK(15)
                    wg_commit();
                    mbar_wait(sbase + OFF_FULL + 16, 0);
                    wg_fence();
                    JOBK(16) JOBK(17) JOBK(18) JOBK(19) JOBK(20) JOBK(21) JOBK(22) JOBK(23)
#undef JOBK
                    wg_commit();
                    wg_wait<0>();
                    const int fidx = (cb * NFRAG + (job / 3) * 2) * 128 + wtid;
                    uint4* dst = scr->wfrag + (par & 1) * (6 * NFRAG * 128) + fidx;
#pragma unroll
                    for (int i = 0; i < 2; i++) {
                        asm volatile("st.relaxed.gpu.global.v4.u32 [%0], {%1, %2, %3, %4};" ::"l"(dst + i * 128),
                                     "r"(pack_neg(ja[8 * i + 0], ja[8 * i + 1])), "r"(pack_neg(ja[8 * i + 2], ja[8 * i + 3])),
                                     "r"(pack_neg(ja[8 * i + 4], ja[8 * i + 5])), "r"(pack_neg(ja[8 * i + 6], ja[8 * i + 7])) : "memory");
                    }
                }
                if (job + npair < NJOBS) asm volatile("bar.sync 4, 384;" ::: "memory");
                if (job != pair) jph ^= 1;
            }
        }

        par &= 1;
        mbar_wait(sbase + OFF_FULL, 0);
        mbar_wait(sbase + OFF_FULL + 8, 0);
        mbar_wait(sbase + OFF_FULL + 16, 0);
        asm volatile("bar.sync 6, 384;" ::: "memory");
        if (cx.signal) {
            mbar_arrive_cluster(cx.empty_tgt);
            mbar_arrive_cluster(cx.empty_tgt + 8);
            mbar_arrive_cluster(cx.empty_tgt + 16);
        }
        auto pack_q = [&]() {
            uint32_t all = 0;
#pragma unroll
            for (int i = 0; i < 16; i++) {
                qp[i] = pack_bf16(acc[2 * i], acc[2 * i + 1]);
                if (i >= 4) all |= qp[i];
            }
            qp[3] |= all & zero;
        };
        bool ready = false;
        uint32_t pu = 0;
#define CHUNK(N, MODE) chunk<N, MODE, false>(acc, W, qp, zero, cx, pu, ready, wg)
#define TCHUNK(N, MODE) chunk<N, MODE, ((N) >= 90 - 6 * SKEW_TILES)>(acc, W, qp, zero, cx, pu, ready, wg)

        const uint4* wsrc = scr->wfrag + (par * 6 + cb) * (NFRAG * 128) + wtid;
        auto load_w = [&](int kc) {
#pragma unroll
            for (int s = 4 * kc; s < 4 * kc + 4; s++) {
                asm volatile("ld.relaxed.gpu.global.v4.u32 {%0, %1, %2, %3}, [%4];"
                             : "=r"(W[4 * s]), "=r"(W[4 * s + 1]), "=r"(W[4 * s + 2]), "=r"(W[4 * s + 3])
                             : "l"(wsrc + s * 128) : "memory");
            }
        };
        auto check_w = [&](int kc) {
            uint32_t* w = kc < 6 ? W + 16 * kc : qp;
            asm volatile(
                "{\n.reg .pred p;\n.reg .u32 m, n;\n"
                "mov.u32 n, 0;\n"
                "CHK_%=:\n"
                "mov.u32 m, %%clock;\n or.b32 m, m, 1;\n min.u32 m, m, %0;\n"
                "min.u32 m, m, %1;\n min.u32 m, m, %2;\n min.u32 m, m, %3;\n min.u32 m, m, %4;\n min.u32 m, m, %5;\n"
                "min.u32 m, m, %6;\n min.u32 m, m, %7;\n min.u32 m, m, %8;\n min.u32 m, m, %9;\n min.u32 m, m, %10;\n"
                "min.u32 m, m, %11;\n min.u32 m, m, %12;\n min.u32 m, m, %13;\n min.u32 m, m, %14;\n min.u32 m, m, %15;\n"
                "setp.ne.u32 p, m, 0;\n"
                "vote.sync.all.pred p, p, 0xffffffff;\n"
                "@p bra.uni OK_%=;\n"
                "add.u32 n, n, 1;\n"
                "setp.gt.u32 p, n, 5000000;\n"
                "@p bra.uni OK_%=;\n"
                "ld.relaxed.gpu.global.v4.u32 {%0, %1, %2, %3}, [%16];\n"
                "ld.relaxed.gpu.global.v4.u32 {%4, %5, %6, %7}, [%16 + 2048];\n"
                "ld.relaxed.gpu.global.v4.u32 {%8, %9, %10, %11}, [%16 + 4096];\n"
                "ld.relaxed.gpu.global.v4.u32 {%12, %13, %14, %15}, [%16 + 6144];\n"
                "bra.uni CHK_%=;\n"
                "OK_%=:\n}"
                : "+r"(w[0]), "+r"(w[1]), "+r"(w[2]), "+r"(w[3]), "+r"(w[4]), "+r"(w[5]), "+r"(w[6]), "+r"(w[7]),
                  "+r"(w[8]), "+r"(w[9]), "+r"(w[10]), "+r"(w[11]), "+r"(w[12]), "+r"(w[13]), "+r"(w[14]), "+r"(w[15])
                : "l"(wsrc + kc * 512) : "memory");
        };
        const uint32_t stage = sbase + OFF_WOUT + wg * WOUT_SLICE + 2 * 8192;
        const uint32_t st_addr = stage + (((lane >> 4) * 8 + (lane & 7)) << 7)
                               + (((((warp & 3) << 1) | ((lane >> 3) & 1)) ^ (lane & 7)) << 4);
        auto publish = [&](int s) {
            if (pair == (NJOBS + s) % npair) {
                uint32_t a[4];
                asm volatile("ldmatrix.sync.aligned.m8n8.x4.trans.shared.b16 {%0, %1, %2, %3}, [%4];"
                             : "=r"(a[0]), "=r"(a[1]), "=r"(a[2]), "=r"(a[3]) : "r"(st_addr + s * 8192) : "memory");
                asm volatile("st.relaxed.gpu.global.v4.u32 [%0], {%1, %2, %3, %4};" ::"l"(wsrc + (24 + s) * 128),
                             "r"(enc_neg(a[0])), "r"(enc_neg(a[1])), "r"(enc_neg(a[2])), "r"(enc_neg(a[3])) : "memory");
            }
        };
        CHUNK(0, COARSE);
        CHUNK(1, COARSE);
        CHUNK(2, COARSE);
        publish(0);
        load_w(0);
        CHUNK(3, COARSE);
        publish(1);
        load_w(1);
        CHUNK(4, COARSE);
        publish(2);
        load_w(2);
        CHUNK(5, COARSE);
        publish(3);
        wg_wait<0>();
        release<5>(cx);
        pack_q();

        auto flush_part = [&](int row, int part) {
            if (part == 0) {
                asm volatile("fence.proxy.async.shared::cta;" ::: "memory");
                named_bar(wg);
            }
            if (wtid == 0) {
                tma_store_2d(&tm_out, cb * 64, row + (part >> 1) * HW + (part & 1) * 16, stage + part * 8192, POLICY_EVICT_FIRST);
                if (part == 3) asm volatile("cp.async.bulk.commit_group;" ::: "memory");
            }
        };
        auto init_acc = [&](int t) {
#pragma unroll
            for (int b = 0; b < 2; b++) {
#pragma unroll
                for (int h = 0; h < 2; h++) {
                    const uint32_t q = qp[t * 4 + b * 2 + h];
                    const float lo = __uint_as_float(q << 16), hi = __uint_as_float(q & 0xffff0000u);
#pragma unroll
                    for (int dy = 0; dy < 2; dy++) {
                        acc[16 * dy + 8 * b + 2 * h]         = dy ? dup(lo, one) : lo;
                        acc[16 * dy + 8 * b + 2 * h + 1]     = dup(lo, one);
                        acc[16 * dy + 8 * b + 4 + 2 * h]     = dy ? dup(hi, one) : hi;
                        acc[16 * dy + 8 * b + 4 + 2 * h + 1] = dup(hi, one);
                    }
                }
            }
        };
        auto stage_tile = [&](int slot) {
            if (wtid == 0) asm volatile("cp.async.bulk.wait_group.read 0;" ::: "memory");
            named_bar(wg);
            wg_wait<0>();
            if (cx.signal) mbar_arrive_cluster(cx.empty_tgt + slot * 8);
#pragma unroll
            for (int i = 0; i < 8; i += 2) {
                stsm_x4_t(st_addr + i * 4096,
                          pack_bf16(acc[4 * i + 0], acc[4 * i + 1]), pack_bf16(acc[4 * i + 2], acc[4 * i + 3]),
                          pack_bf16(acc[4 * i + 4], acc[4 * i + 5]), pack_bf16(acc[4 * i + 6], acc[4 * i + 7]));
            }
        };

        auto load_wo = [&]() {
#pragma unroll
            for (int s = 0; s < 4; s++) {
                asm volatile("ld.global.ca.v4.u32 {%0, %1, %2, %3}, [%4];"
                             : "=r"(qp[4 * s]), "=r"(qp[4 * s + 1]), "=r"(qp[4 * s + 2]), "=r"(qp[4 * s + 3])
                             : "l"(wsrc + (24 + s) * 128) : "memory");
            }
        };

        init_acc(0);
        check_w(0);
        load_w(3);
        load_w(4);
        CHUNK(6, FINE);
        check_w(1);
        CHUNK(7, FINE);
        check_w(2);
        CHUNK(8, FINE);
        check_w(3);
        load_w(5);
        CHUNK(9, FINE);
        check_w(4);
        CHUNK(10, FINE);
        check_w(5);
        CHUNK(11, FINE);

        int seg = pair;
        int prow = seg_row(seg);
        while (true) {
            stage_tile(slot_of<11>());
            init_acc(1);
            CHUNK(12, FINE);
            flush_part(prow, 0);
            CHUNK(13, FINE);
            CHUNK(14, FINE);
            flush_part(prow, 1);
            CHUNK(15, FINE);
            flush_part(prow, 2);
            CHUNK(16, FINE);
            flush_part(prow, 3);
            CHUNK(17, FINE);
            seg += npair;
            prow = seg_row(seg);
            stage_tile(slot_of<17>());
            init_acc(2);
            CHUNK(18, FINE);
            flush_part(prow, 0);
            CHUNK(19, FINE);
            CHUNK(20, FINE);
            flush_part(prow, 1);
            CHUNK(21, FINE);
            flush_part(prow, 2);
            CHUNK(22, FINE);
            flush_part(prow, 3);
            CHUNK(23, FINE);
            seg += npair;
            prow = seg_row(seg);
            stage_tile(slot_of<23>());
            init_acc(3);
            CHUNK(24, FINE);
            flush_part(prow, 0);
            CHUNK(25, FINE);
            load_wo();
            CHUNK(26, FINE);
            flush_part(prow, 1);
            CHUNK(27, FINE);
            flush_part(prow, 2);
            CHUNK(28, FINE);
            flush_part(prow, 3);
            CHUNK(29, FINE);
            seg += npair;
            prow = seg_row(seg);
            const bool tail = seg + 9 * npair >= NSEG;
            stage_tile(slot_of<29>());
            CHUNK(30, COARSE);
            flush_part(prow, 0);
            CHUNK(31, COARSE);
            check_w(6);
            CHUNK(32, COARSE_REG);
            if (tail) flush_part(prow, 2);
            CHUNK(33, COARSE_REG);
            flush_part(prow, 1);
            CHUNK(34, COARSE_REG);
            if (tail) flush_part(prow, 3);
            CHUNK(35, COARSE_REG);
            if (tail) break;
            wg_wait<0>();
            release<35>(cx);
            pack_q();
            init_acc(0);
            CHUNK(36, FINE);
            flush_part(prow, 2);
            CHUNK(37, FINE);
            CHUNK(38, FINE);
            CHUNK(39, FINE);
            flush_part(prow, 3);
            CHUNK(40, FINE);
            CHUNK(41, FINE);
            seg += npair;
            prow = seg_row(seg);
            pu ^= 1;
        }

        const uint32_t park = stage + wtid * 16;
        if (wtid == 0) asm volatile("cp.async.bulk.wait_group.read 0;" ::: "memory");
        named_bar(wg);
        wg_wait<0>();
        release<35>(cx);
#pragma unroll
        for (int i = 0; i < 4; i++) {
            asm volatile("st.shared.v4.u32 [%0], {%1, %2, %3, %4};" ::"r"(park + i * 8192),
                         "r"(pack_bf16(acc[8 * i + 0], acc[8 * i + 1])), "r"(pack_bf16(acc[8 * i + 2], acc[8 * i + 3])),
                         "r"(pack_bf16(acc[8 * i + 4], acc[8 * i + 5])), "r"(pack_bf16(acc[8 * i + 6], acc[8 * i + 7])) : "memory");
        }
        CHUNK(36, COARSE);
        CHUNK(37, COARSE);
        CHUNK(38, COARSE_REG);
        CHUNK(39, COARSE_REG);
        CHUNK(40, COARSE_REG);
        CHUNK(41, COARSE_REG);
        wg_wait<0>();
        release<41>(cx);
        pack_q();

        auto send = [&](auto mc) {
            constexpr int m = decltype(mc)::v, off = piece_off(m);
            if (m % 4 == 0) prow = seg_row(seg + (1 + m / 4) * npair);
            if (wtid == 0) {
                tma_store_2d(&tm_out, cb * 64, prow + (m / 2 % 2) * HW + (m % 2) * 16, stage - 16384 + off, POLICY_EVICT_FIRST);
                if (m % 4 == 3) asm volatile("cp.async.bulk.commit_group;" ::: "memory");
            }
        };
        auto after = [&](auto tc, auto pc) {
            constexpr int t = decltype(tc)::v, pos = decltype(pc)::v, m = sched_sent(t, pos), n = sched_sent(t, pos + 1) - m;
            if (pos == 0 && t > 0) {
                if (t == 6 && wtid == 0) asm volatile("cp.async.bulk.wait_group.read %0;" ::"n"(t == 6 ? m / 4 - 2 : 0) : "memory");
                asm volatile("fence.proxy.async.shared::cta;" ::: "memory");
                named_bar(wg);
            }
            if (n > 0) send(IC<m>{});
            if (n > 1) send(IC<m + 1>{});
            if (t == 3 && pos == 1) {
#pragma unroll
                for (int i = 0; i < 4; i++) {
                    asm volatile("ld.shared.v4.u32 {%0, %1, %2, %3}, [%4];"
                                 : "=r"(qp[4 * i]), "=r"(qp[4 * i + 1]), "=r"(qp[4 * i + 2]), "=r"(qp[4 * i + 3])
                                 : "r"(park + i * 8192) : "memory");
                }
            }
        };
        auto stage_piece = [&](auto mc) {
            constexpr int off = piece_off(decltype(mc)::v), i = decltype(mc)::v % 4 * 8;
            stsm_x4_t(st_addr - 16384 + off, pack_bf16(acc[i + 0], acc[i + 1]), pack_bf16(acc[i + 2], acc[i + 3]),
                                             pack_bf16(acc[i + 4], acc[i + 5]), pack_bf16(acc[i + 6], acc[i + 7]));
        };
#define TAIL_TILE(T)                                                                                          \
        init_acc(T % 4);                                                                                      \
        TCHUNK(42 + 6 * T, FINE); after(IC<T>{}, IC<0>{});                                                    \
        TCHUNK(43 + 6 * T, FINE); after(IC<T>{}, IC<1>{});                                                    \
        TCHUNK(44 + 6 * T, FINE); after(IC<T>{}, IC<2>{});                                                    \
        TCHUNK(45 + 6 * T, FINE); after(IC<T>{}, IC<3>{});                                                    \
        TCHUNK(46 + 6 * T, FINE); after(IC<T>{}, IC<4>{});                                                    \
        TCHUNK(47 + 6 * T, FINE); after(IC<T>{}, IC<5>{});                                                    \
        wg_wait<0>();                                                                                         \
        release<47 + 6 * T>(cx);                                                                              \
        stage_piece(IC<4 * T>{}); stage_piece(IC<4 * T + 1>{}); stage_piece(IC<4 * T + 2>{}); stage_piece(IC<4 * T + 3>{});
        TAIL_TILE(0) TAIL_TILE(1) TAIL_TILE(2) TAIL_TILE(3) TAIL_TILE(4) TAIL_TILE(5) TAIL_TILE(6) TAIL_TILE(7)
#undef TAIL_TILE
#undef TCHUNK
#undef CHUNK
        after(IC<8>{}, IC<0>{});
        constexpr int sent = sched_sent(8, 0);
        static_assert(sent >= 24, "");
        if (sent <= 24) send(IC<24>{});
        if (sent <= 25) send(IC<25>{});
        if (sent <= 26) send(IC<26>{});
        if (sent <= 27) send(IC<27>{});
        send(IC<28>{}); send(IC<29>{}); send(IC<30>{}); send(IC<31>{});
        if (wtid == 0) asm volatile("cp.async.bulk.wait_group.read 0;" ::: "memory");
    } else {
        asm volatile("setmaxnreg.dec.sync.aligned.u32 32;");
        if (warp == 12) {
            asm volatile("bar.sync 5, 448;" ::: "memory");
            if (elect_one()) {
                const int g1 = (pair + 1) % 3, g2 = (pair + 2) % 3;
#pragma unroll 1
                for (int kc = 0; kc < 6; kc++) {
                    const uint32_t bar = sbase + OFF_FULL + (3 + kc) * 8;
                    mbar_expect_tx(bar, (kc & 1) ? SLOT_BYTES : 5 * SLOT_BYTES);
                    tma_load_5d(sbase + OFF_RING + (3 + kc) * SLOT_BYTES, &tm_p8, kc * 64, pair * 2, 0, bar);
                    if (!(kc & 1)) {
                        tma_load_2d(sbase + OFF_WOUT + g1 * WOUT_SLICE + kc * 8192, &tm_wo, rank * 192 + g1 * 64, kc * 64, bar);
                        tma_load_2d(sbase + OFF_WOUT + g2 * WOUT_SLICE + kc * 8192, &tm_wo, rank * 192 + g2 * 64, kc * 64, bar);
                    }
                }
            }
            __syncwarp();
        }
        asm volatile("barrier.cluster.wait.aligned;" ::: "memory");
        if (warp == 12) {
            if ((sbase & 0x3FFFFu) != SMEM_BASE) asm volatile("trap;");
            const uint32_t dst0 = sbase + OFF_RING + rank * 4096;
            uint32_t so = 9 * 8, ph = 1, step = 6;
            auto next_slot = [&]() {
                so += 8;
                if (so == NSLOTS * 8) { so = 0; ph ^= 1; }
            };
            unsigned mytiles = 0, seen = 0;
            auto look = [&]() {
                asm volatile("ld.relaxed.gpu.global.u32 %0, [%1];" : "=r"(seen) : "l"(&scr->prog) : "memory");
            };
            auto tile = [&](bool coarse, int coord, uint64_t pol, bool last) {
                if (rank == 0 && mytiles >= GOV_START) {
                    const unsigned need = mytiles * npair - 2 * max(GOV_TIGHT - (int)mytiles, 0);
                    unsigned spins = 0;
                    while (__any_sync(0xffffffffu, (int)(need - seen) > 0) && ++spins < 100000u) look();
                }
                mytiles++;
#pragma unroll
                for (int kc = 0; kc < 6; kc++) {
                    const uint32_t bar = sbase + OFF_FULL + so, dst = dst0 + so * (SLOT_BYTES / 8);
                    mbar_wait_bounded(sbase + OFF_EMPTY + so, ph);
                    step++;
                    if (elect_one()) {
                        mbar_expect_tx(bar, SLOT_BYTES);
                        if (coarse) tma_load_5d_mc(dst, &tm_p, kc * 64, pair * 2, coord, bar, pol);
                        else        tma_load_2d_mc(dst, &tm_c, kc * 64, coord, bar, pol);
                        asm volatile("st.volatile.shared.u32 [%0], %1;" ::"r"(sbase + OFF_PACE), "r"(step) : "memory");
                    }
                    if (kc == 0 && rank == 0 && lane == 0 && !last)
                        asm volatile("red.relaxed.gpu.global.add.u32 [%0], 1;" ::"l"(&scr->prog) : "memory");
                    next_slot();
                    if (kc == 3 && rank == 0) look();
                }
            };
            const int ntiles = nfine + nfine / 4;
#pragma unroll 1
            for (int i = 1; i < ntiles; i++) {
                int j;
                const bool coarse = tile_of(i, nfine, j);
                tile(coarse, coarse ? j + 2 * rank : seg_row(j * npair + pair) + rank * HW,
                     i >= ntiles - EF_TILES ? POLICY_EVICT_FIRST : POLICY_EVICT_NORMAL, i + 1 == ntiles);
            }
            if (rank == 0 && lane == 0) {
                if (atomicAdd(&scr->prog, 1u) + 1 == mytiles * npair) {
                    asm volatile("st.relaxed.gpu.global.u32 [%0], 0;" ::"l"(&scr->prog) : "memory");
                    asm volatile("red.relaxed.gpu.global.add.u32 [%0], 1;" ::"l"(&scr->epoch) : "memory");
                }
            }
            __syncwarp();
#pragma unroll 1
            for (int s = 0; s < NSLOTS; s++) {
                mbar_wait_bounded(sbase + OFF_EMPTY + so, ph);
                next_slot();
            }
        } else if (warp == 13) {
            auto wait_pace = [&](int need) {
                unsigned spins = 0;
                while (true) {
                    uint32_t v;
                    asm volatile("ld.volatile.shared.u32 %0, [%1];" : "=r"(v) : "r"(sbase + OFF_PACE) : "memory");
                    if ((int)v >= need || ++spins > 4000000u) break;
                    __nanosleep(20);
                }
            };
            if (lane == 0) mbar_expect_tx(sbase + OFF_NB, 12 * 512);
#pragma unroll 1
            for (int k = 0; k < 12; k++) {
                const int j = k < 6 ? 2 : 3;
                wait_pace(PF_FIRST + k * 3 / 4);
                if (lane == 0)
                    tma_load_2d(sbase + OFF_SINK, &tm_cf, 0, (seg_row(j * npair + pair) + rank * HW) * 6 + (k - (j - 2) * 6) * 32,
                                sbase + OFF_NB);
            }
#pragma unroll 1
            for (int i = 5; i < nfine + nfine / 4; i++) {
                int j;
                const char *b0, *b1;
                if (tile_of(i, nfine, j)) {
                    b0 = (const char*)p_ptr + (size_t)((j + 2 * rank) * npair + pair) * (16 * C * 2);
                    b1 = b0 + (size_t)npair * (16 * C * 2);
                } else {
                    b0 = (const char*)c_ptr + (size_t)(seg_row(j * npair + pair) + rank * HW) * (C * 2);
                    b1 = b0 + 16 * C * 2;
                }
                wait_pace(6 * i - max(PF_LEAD0 - max(i - PF_DECAY, 0), PF_LEAD));
#pragma unroll
                for (int k = 0; k < 6; k++) {
                    asm volatile("prefetch.global.L2 [%0];" ::"l"((k < 3 ? b0 : b1) + lane * 128 + (k % 3) * 4096) : "memory");
                    __nanosleep(PF_GAP);
                }
            }
            mbar_wait_bounded(sbase + OFF_NB, 0);
        } else if (warp == 15) {
            uint32_t par, v;
            asm volatile("ld.relaxed.gpu.global.u32 %0, [%1];" : "=r"(par) : "l"(&scr->epoch) : "memory");
            uint4* clr = scr->wfrag + (~par & 1) * (6 * NFRAG * 128);
            unsigned spins = 0;
            do {
                __nanosleep(500);
                asm volatile("ld.volatile.shared.u32 %0, [%1];" : "=r"(v) : "r"(sbase + OFF_PACE) : "memory");
            } while (v < CLR_AT && ++spins < 100000u);
            for (int i = blockIdx.x * 32 + lane; i < 6 * NFRAG * 128; i += npair * 64) clr[i] = make_uint4(0u, 0u, 0u, 0u);
        }
    }
}

typedef CUresult (*EncodeFn)(CUtensorMap*, CUtensorMapDataType, cuuint32_t, void*, const cuuint64_t*, const cuuint64_t*,
                             const cuuint32_t*, const cuuint32_t*, CUtensorMapInterleave, CUtensorMapSwizzle,
                             CUtensorMapL2promotion, CUtensorMapFloatOOBfill);

void encode(EncodeFn fn, CUtensorMap* tm, const void* ptr, int rank, const cuuint64_t* dims, const cuuint64_t* strides,
            const cuuint32_t* box, CUtensorMapSwizzle swizzle = CU_TENSOR_MAP_SWIZZLE_128B,
            CUtensorMapL2promotion promotion = CU_TENSOR_MAP_L2_PROMOTION_NONE) {
    const cuuint32_t es[5] = {1, 1, 1, 1, 1};
    fn(tm, CU_TENSOR_MAP_DATA_TYPE_BFLOAT16, (cuuint32_t)rank, const_cast<void*>(ptr), dims, strides, box, es,
       CU_TENSOR_MAP_INTERLEAVE_NONE, swizzle, promotion, CU_TENSOR_MAP_FLOAT_OOB_FILL_NONE);
}

}

extern "C" void kernel_launch(void* const* d_in, const int* in_sizes, int n_in, void* d_out, int out_size) {
    (void)in_sizes; (void)n_in; (void)out_size;
    const __nv_bfloat16* c_fine   = (const __nv_bfloat16*)d_in[0];
    const __nv_bfloat16* p_coarse = (const __nv_bfloat16*)d_in[1];
    const __nv_bfloat16* w_lat    = (const __nv_bfloat16*)d_in[2];
    const __nv_bfloat16* w_out    = (const __nv_bfloat16*)d_in[3];

    static EncodeFn fn = nullptr;
    static int np = 0;
    static Scratch* scr = nullptr;
    if (!fn) {
        void* p = nullptr;
        cudaDriverEntryPointQueryResult qr;
        cudaGetDriverEntryPoint("cuTensorMapEncodeTiled", &p, cudaEnableDefault, &qr);
        fn = (EncodeFn)p;
        cudaGetSymbolAddress((void**)&scr, g_scratch);
        cudaFuncSetAttribute(fpn_kernel<NPAIRS>, cudaFuncAttributeMaxDynamicSharedMemorySize, SMEM_BYTES);
        cudaFuncSetAttribute(fpn_kernel<0>, cudaFuncAttributeMaxDynamicSharedMemorySize, SMEM_BYTES);
        cudaLaunchConfig_t cfg = {};
        cfg.gridDim = dim3(2); cfg.blockDim = dim3(NTHREADS); cfg.dynamicSmemBytes = SMEM_BYTES;
        cudaLaunchAttribute at[1];
        at[0].id = cudaLaunchAttributeClusterDimension;
        at[0].val.clusterDim.x = 2; at[0].val.clusterDim.y = 1; at[0].val.clusterDim.z = 1;
        cfg.attrs = at; cfg.numAttrs = 1;
        if (cudaOccupancyMaxActiveClusters(&np, fpn_kernel<0>, &cfg) != cudaSuccess || np < 1) np = 1;
        if (np > NPAIRS) np = NPAIRS;
        while ((NSEG / 4) % np) np--;
    }

    CUtensorMap tm_cf, tm_c, tm_p, tm_wl3, tm_out, tm_p8, tm_wo;
    {
        const cuuint64_t dims[2] = {(cuuint64_t)C, (cuuint64_t)NPIX};
        const cuuint64_t str[1]  = {(cuuint64_t)C * 2};
        const cuuint32_t box_in[2]  = {64, 32};
        const cuuint32_t box_out[2] = {64, 16};
        encode(fn, &tm_c, c_fine, 2, dims, str, box_in);
        encode(fn, &tm_out, d_out, 2, dims, str, box_out);
    }
    {
        const cuuint64_t dims[5] = {(cuuint64_t)C, 2, 4, (cuuint64_t)(2 * np), (cuuint64_t)(NSEG / np)};
        const cuuint64_t str[4]  = {(cuuint64_t)4 * C * 2, (cuuint64_t)C * 2, (cuuint64_t)8 * C * 2, (cuuint64_t)np * 16 * C * 2};
        const cuuint32_t box[5]  = {64, 2, 4, 2, 2};
        encode(fn, &tm_p, p_coarse, 5, dims, str, box);
        const cuuint32_t box8[5] = {64, 2, 4, 2, 4};
        encode(fn, &tm_p8, p_coarse, 5, dims, str, box8);
    }
    {
        const cuuint64_t dims[2] = {(cuuint64_t)C, (cuuint64_t)C};
        const cuuint64_t str[1]  = {(cuuint64_t)C * 2};
        const cuuint32_t box[2] = {64, 128};
        encode(fn, &tm_wo, w_out, 2, dims, str, box);
    }
    {
        const cuuint64_t dims[3] = {64, (cuuint64_t)C, 6};
        const cuuint64_t str[2]  = {(cuuint64_t)C * 2, 128};
        const cuuint32_t box[3]  = {64, 32, 2};
        encode(fn, &tm_wl3, w_lat, 3, dims, str, box);
    }
    {
        const cuuint64_t dims[2] = {64, (cuuint64_t)NPIX * 6};
        const cuuint64_t str[1]  = {128};
        const cuuint32_t box[2]  = {8, 32};
        encode(fn, &tm_cf, c_fine, 2, dims, str, box, CU_TENSOR_MAP_SWIZZLE_NONE, CU_TENSOR_MAP_L2_PROMOTION_L2_128B);
    }
    auto kernel = np == NPAIRS ? fpn_kernel<NPAIRS> : fpn_kernel<0>;
    kernel<<<2 * np, NTHREADS, SMEM_BYTES>>>(scr, c_fine, p_coarse, NSEG / np, 1.0f, 0u,
                                             tm_wo, tm_wl3, tm_p8, tm_c, tm_p, tm_out, tm_cf);
}
```

```cpp
#include <cuda_runtime.h>
#include <cuda_bf16.h>
#include <cuda.h>
#include <stdint.h>

namespace {

constexpr int C          = 384;
constexpr int HW         = 384;
constexpr int NPIX       = HW * HW;
constexpr int NSEG       = NPIX / 64;
constexpr int NJOBS      = 36;

constexpr int NFRAG      = 28;
constexpr int NSLOTS     = 10;
constexpr int NPAIRS     = 64;
constexpr int PF_LEAD    = 5;
constexpr int PF_LEAD0   = 18;
constexpr int PF_DECAY   = 12;
constexpr int PF_FIRST   = 11;
constexpr int PF_GAP     = 50;
constexpr int GOV_START  = 12;
constexpr int GOV_TIGHT  = 26;
constexpr int EF_TILES   = 13;
constexpr int SCHED      = 2266;
constexpr int CLR_AT     = 20;

constexpr int SLOT_BYTES  = 8192;
constexpr int WOUT_SLICE  = 384 * 128;
constexpr int OFF_WOUT    = 0;
constexpr int OFF_RING    = 3 * WOUT_SLICE;
constexpr int OFF_FULL    = OFF_RING + NSLOTS * SLOT_BYTES;
constexpr int OFF_EMPTY   = OFF_FULL + 8 * NSLOTS;
constexpr int OFF_JB2     = OFF_EMPTY + 8 * NSLOTS;
constexpr int OFF_PACE    = OFF_JB2 + 8;
constexpr int OFF_NB      = OFF_PACE + 8;
constexpr int OFF_SINK    = (OFF_NB + 8 + 127) / 128 * 128;
constexpr int SMEM_BYTES  = OFF_SINK + 512;
static_assert(SMEM_BYTES <= 232448, "smem");
static_assert(NSLOTS == 10, "a unit (30 ring items) must be an odd number of rounds of the ring");

constexpr int      SMEM_BASE = 1024;
constexpr uint64_t DESC_RING = 0x4000004000010000ull + ((SMEM_BASE + OFF_RING) >> 4);

constexpr int NTHREADS = 512;
constexpr uint64_t POLICY_EVICT_FIRST  = 0x12F0000000000000ull;
constexpr uint64_t POLICY_EVICT_NORMAL = 0x1000000000000000ull;

struct Scratch {
    uint4    wfrag[2 * 6 * NFRAG * 128];
    unsigned epoch;
    unsigned pad0[31];
    unsigned prog;
};
__device__ Scratch g_scratch;

__device__ __forceinline__ uint32_t smem_u32(const void* p) { return (uint32_t)__cvta_generic_to_shared(p); }

__device__ __forceinline__ void mbar_init(uint32_t bar, uint32_t cnt) {
    asm volatile("mbarrier.init.shared::cta.b64 [%0], %1;" ::"r"(bar), "r"(cnt) : "memory");
}
__device__ __forceinline__ void mbar_expect_tx(uint32_t bar, uint32_t bytes) {
    asm volatile("mbarrier.arrive.expect_tx.shared::cta.b64 _, [%0], %1;" ::"r"(bar), "r"(bytes) : "memory");
}
__device__ __forceinline__ void mbar_wait_bounded(uint32_t bar, uint32_t parity) {
    asm volatile(
        "{\n"
        ".reg .pred p;\n"
        ".reg .u32 n;\n"
        "mbarrier.try_wait.parity.shared::cta.b64 p, [%0], %1;\n"
        "@p bra DONE_%=;\n"
        "mov.u32 n, 0;\n"
        "WAIT_%=:\n"
        "mbarrier.try_wait.parity.shared::cta.b64 p, [%0], %1;\n"
        "@p bra DONE_%=;\n"
        "add.u32 n, n, 1;\n"
        "setp.lt.u32 p, n, 4000000;\n"
        "@p bra WAIT_%=;\n"
        "trap;\n"
        "DONE_%=:\n"
        "}\n" ::"r"(bar), "r"(parity) : "memory");
}
__device__ __forceinline__ void mbar_wait(uint32_t bar, uint32_t parity) {
    asm volatile(
        "{\n"
        ".reg .pred p;\n"
        "WAIT_%=:\n"
        "mbarrier.try_wait.parity.shared::cta.b64 p, [%0], %1;\n"
        "@!p bra WAIT_%=;\n"
        "}\n" ::"r"(bar), "r"(parity) : "memory");
}
__device__ __forceinline__ bool mbar_try(uint32_t bar, uint32_t parity) {
    uint32_t r;
    asm volatile("{\n.reg .pred p;\nmbarrier.test_wait.parity.shared::cta.b64 p, [%1], %2;\nselp.u32 %0, 1, 0, p;\n}\n"
                 : "=r"(r) : "r"(bar), "r"(parity) : "memory");
    return r != 0;
}
__device__ __forceinline__ void mbar_arrive_cluster(uint32_t cluster_addr) {
    asm volatile("mbarrier.arrive.shared::cluster.b64 _, [%0];" ::"r"(cluster_addr) : "memory");
}
__device__ __forceinline__ uint32_t mapa(uint32_t addr, uint32_t rank) {
    uint32_t r;
    asm("mapa.shared::cluster.u32 %0, %1, %2;" : "=r"(r) : "r"(addr), "r"(rank));
    return r;
}
__device__ __forceinline__ void named_bar(int wg) {
    asm volatile("bar.sync %0, 128;" ::"r"(wg + 1) : "memory");
}

__device__ __forceinline__ void tma_load_2d(uint32_t dst, const CUtensorMap* tm, int c0, int c1, uint32_t bar) {
    asm volatile("cp.async.bulk.tensor.2d.shared::cluster.global.mbarrier::complete_tx::bytes [%0], [%1, {%2, %3}], [%4];"
                 ::"r"(dst), "l"(tm), "r"(c0), "r"(c1), "r"(bar) : "memory");
}
__device__ __forceinline__ void tma_load_3d(uint32_t dst, const CUtensorMap* tm, int c0, int c1, int c2, uint32_t bar) {
    asm volatile("cp.async.bulk.tensor.3d.shared::cluster.global.mbarrier::complete_tx::bytes [%0], [%1, {%2, %3, %4}], [%5];"
                 ::"r"(dst), "l"(tm), "r"(c0), "r"(c1), "r"(c2), "r"(bar) : "memory");
}
__device__ __forceinline__ void tma_load_5d(uint32_t dst, const CUtensorMap* tm, int c0, int c3, int c4, uint32_t bar) {
    asm volatile("cp.async.bulk.tensor.5d.shared::cluster.global.mbarrier::complete_tx::bytes [%0], [%1, {%2, 0, 0, %3, %4}], [%5];"
                 ::"r"(dst), "l"(tm), "r"(c0), "r"(c3), "r"(c4), "r"(bar) : "memory");
}
__device__ __forceinline__ void tma_load_2d_mc(uint32_t dst, const CUtensorMap* tm, int c0, int c1, uint32_t bar, uint64_t pol) {
    asm volatile("cp.async.bulk.tensor.2d.shared::cluster.global.mbarrier::complete_tx::bytes.multicast::cluster.L2::cache_hint"
                 " [%0], [%1, {%2, %3}], [%4], %5, %6;"
                 ::"r"(dst), "l"(tm), "r"(c0), "r"(c1), "r"(bar), "h"((uint16_t)3), "l"(pol) : "memory");
}
__device__ __forceinline__ void tma_load_5d_mc(uint32_t dst, const CUtensorMap* tm, int c0, int c3, int c4, uint32_t bar, uint64_t pol) {
    asm volatile("cp.async.bulk.tensor.5d.shared::cluster.global.mbarrier::complete_tx::bytes.multicast::cluster.L2::cache_hint"
                 " [%0], [%1, {%2, 0, 0, %3, %4}], [%5], %6, %7;"
                 ::"r"(dst), "l"(tm), "r"(c0), "r"(c3), "r"(c4), "r"(bar), "h"((uint16_t)3), "l"(pol) : "memory");
}
__device__ __forceinline__ void tma_store_2d(const CUtensorMap* tm, int c0, int c1, uint32_t src, uint64_t pol) {
    asm volatile("cp.async.bulk.tensor.2d.global.shared::cta.bulk_group.L2::cache_hint [%0, {%1, %2}], [%3], %4;"
                 ::"l"(tm), "r"(c0), "r"(c1), "r"(src), "l"(pol) : "memory");
}
__device__ __forceinline__ bool elect_one() {
    uint32_t r;
    asm volatile("{\n.reg .pred p;\nelect.sync _|p, 0xffffffff;\nselp.u32 %0, 1, 0, p;\n}" : "=r"(r));
    return r != 0;
}
__device__ __forceinline__ void prefetch_tmap(const CUtensorMap* tm) {
    asm volatile("prefetch.tensormap [%0];" ::"l"(tm) : "memory");
}

__device__ __forceinline__ void wg_fence()  { asm volatile("wgmma.fence.sync.aligned;" ::: "memory"); }
__device__ __forceinline__ void wg_commit() { asm volatile("wgmma.commit_group.sync.aligned;" ::: "memory"); }
template <int N> __device__ __forceinline__ void wg_wait() { asm volatile("wgmma.wait_group.sync.aligned %0;" ::"n"(N) : "memory"); }

#define ACC16(a)                                                                                              \
    "+f"(a[0]), "+f"(a[1]), "+f"(a[2]), "+f"(a[3]), "+f"(a[4]), "+f"(a[5]), "+f"(a[6]), "+f"(a[7]),           \
    "+f"(a[8]), "+f"(a[9]), "+f"(a[10]), "+f"(a[11]), "+f"(a[12]), "+f"(a[13]), "+f"(a[14]), "+f"(a[15])
#define ACC32(a)                                                                                              \
    ACC16(a),                                                                                                 \
    "+f"(a[16]), "+f"(a[17]), "+f"(a[18]), "+f"(a[19]), "+f"(a[20]), "+f"(a[21]), "+f"(a[22]), "+f"(a[23]),   \
    "+f"(a[24]), "+f"(a[25]), "+f"(a[26]), "+f"(a[27]), "+f"(a[28]), "+f"(a[29]), "+f"(a[30]), "+f"(a[31])
#define ACC16_STR "{%0, %1, %2, %3, %4, %5, %6, %7, %8, %9, %10, %11, %12, %13, %14, %15}"
#define ACC32_STR                                                                                             \
    "{%0, %1, %2, %3, %4, %5, %6, %7, %8, %9, %10, %11, %12, %13, %14, %15, "                                 \
    "%16, %17, %18, %19, %20, %21, %22, %23, %24, %25, %26, %27, %28, %29, %30, %31}"

template <int BOFF>
__device__ __forceinline__ void wgmma_rs(float (&d)[32], uint32_t a0, uint32_t a1, uint32_t a2, uint32_t a3) {
    asm volatile("{\n.reg .b64 db;\n"
                 "mov.b64 db, %36;\n"
                 "wgmma.mma_async.sync.aligned.m64n64k16.f32.bf16.bf16 " ACC32_STR
                 ", {%32, %33, %34, %35}, db, 1, -1, 1, 0;\n}"
                 : ACC32(d) : "r"(a0), "r"(a1), "r"(a2), "r"(a3), "n"(DESC_RING + BOFF));
}
template <int ACCUM, int AOFF, int BOFF>
__device__ __forceinline__ void wgmma_ss(float (&d)[32], uint32_t da_lo) {
    asm volatile("{\n.reg .b64 da, db;\n.reg .b32 lo;\n"
                 "add.u32 lo, %32, %34;\nmov.b64 da, {lo, 0x40000040};\n"
                 "mov.b64 db, %35;\n"
                 "wgmma.mma_async.sync.aligned.m64n64k16.f32.bf16.bf16 " ACC32_STR
                 ", da, db, %33, 1, 1, 1, 0;\n}"
                 : ACC32(d) : "r"(da_lo), "n"(ACCUM), "n"(AOFF), "n"(DESC_RING + BOFF));
}
template <int ACCUM, int AOFF, int BOFF>
__device__ __forceinline__ void wgmma_ss32(float (&d)[16], uint32_t da_lo) {
    asm volatile("{\n.reg .b64 da, db;\n.reg .b32 lo;\n"
                 "add.u32 lo, %16, %18;\nmov.b64 da, {lo, 0x40000040};\n"
                 "mov.b64 db, %19;\n"
                 "wgmma.mma_async.sync.aligned.m64n32k16.f32.bf16.bf16 " ACC16_STR
                 ", da, db, %17, 1, 1, 1, 0;\n}"
                 : ACC16(d) : "r"(da_lo), "n"(ACCUM), "n"(AOFF), "n"(DESC_RING + BOFF));
}
__device__ __forceinline__ uint32_t desc_lo(uint32_t addr) { return ((addr & 0x3FFFFu) >> 4) | (1u << 16); }
__device__ __forceinline__ uint32_t pack_bf16(float lo, float hi) {
    uint32_t r;
    asm("cvt.rn.bf16x2.f32 %0, %1, %2;" : "=r"(r) : "f"(hi), "f"(lo));
    return r;
}
__device__ __forceinline__ uint32_t enc_neg(uint32_t pair) {
    const uint32_t v = pair ^ 0x80008000u;
    return v == 0u ? 0x80008000u : v;
}
__device__ __forceinline__ uint32_t pack_neg(float lo, float hi) { return enc_neg(pack_bf16(lo, hi)); }
__device__ __forceinline__ float dup(float x, float one) {
    float r;
    asm volatile("mul.f32 %0, %1, %2;" : "=f"(r) : "f"(x), "f"(one));
    return r;
}
__device__ __forceinline__ void stsm_x4_t(uint32_t addr, uint32_t r0, uint32_t r1, uint32_t r2, uint32_t r3) {
    asm volatile("stmatrix.sync.aligned.m8n8.x4.trans.shared.b16 [%0], {%1, %2, %3, %4};"
                 ::"r"(addr), "r"(r0), "r"(r1), "r"(r2), "r"(r3) : "memory");
}

struct Ctx {
    uint32_t sbase;
    uint32_t da0;
    uint32_t empty_tgt;
    bool     signal;
};

template <int N> __device__ __forceinline__ constexpr uint32_t slot_of() { return (3 + N) % NSLOTS; }
template <int N> __device__ __forceinline__ uint32_t phase_of(uint32_t pu) { return pu ^ (((3 + N) / NSLOTS) & 1); }
template <int N> __device__ __forceinline__ void release(const Ctx& cx) {
    if (cx.signal) mbar_arrive_cluster(cx.empty_tgt + slot_of<N>() * 8);
}

enum { FINE, COARSE, COARSE_REG };
template <int N, int MODE, bool SKEW>
__device__ __forceinline__ void chunk(float (&acc)[32], const uint32_t (&W)[96], const uint32_t (&A)[16], uint32_t zero,
                                      const Ctx& cx, uint32_t pu, bool& ready, int wg) {
    constexpr int KC = N % 6;
    constexpr int B  = slot_of<N>() * 512;
    if (!ready) mbar_wait(cx.sbase + OFF_FULL + slot_of<N>() * 8, phase_of<N>(pu));
    ready = mbar_try(cx.sbase + OFF_FULL + slot_of<N + 1>() * 8, phase_of<N + 1>(pu));
    if (SKEW) {
        const int id = 8 + ((N / 6) & 1) * 4 + wg;
        if (KC == 2 && wg > 0) asm volatile("bar.sync %0, 256;" ::"r"(id - 1) : "memory");
        if (KC == 4 && wg < 2) asm volatile("bar.arrive %0, 256;" ::"r"(id) : "memory");
    }
    if (MODE == FINE) {
        wg_fence();
        wgmma_rs<B + 0>(acc, W[KC * 16 + 0],  W[KC * 16 + 1],  W[KC * 16 + 2],  W[KC * 16 + 3]);
        wgmma_rs<B + 2>(acc, W[KC * 16 + 4],  W[KC * 16 + 5],  W[KC * 16 + 6],  W[KC * 16 + 7]);
        wgmma_rs<B + 4>(acc, W[KC * 16 + 8],  W[KC * 16 + 9],  W[KC * 16 + 10], W[KC * 16 + 11]);
        wgmma_rs<B + 6>(acc, W[KC * 16 + 12], W[KC * 16 + 13], W[KC * 16 + 14], W[KC * 16 + 15]);
    } else {
        if (MODE == COARSE) {
            wg_fence();
            wgmma_ss<(KC > 0), KC * 4 * 128, B>(acc, cx.da0);
        } else {
            uint32_t a[4];
            asm volatile("{\n.reg .u32 z;\nmov.u32 z, %%clock;\nand.b32 z, z, %8;\n"
                         "xor.b32 %0, %4, z;\nxor.b32 %1, %5, z;\nxor.b32 %2, %6, z;\nxor.b32 %3, %7, z;\n}"
                         : "=r"(a[0]), "=r"(a[1]), "=r"(a[2]), "=r"(a[3])
                         : "r"(A[((KC + 2) & 3) * 4]), "r"(A[((KC + 2) & 3) * 4 + 1]), "r"(A[((KC + 2) & 3) * 4 + 2]),
                           "r"(A[((KC + 2) & 3) * 4 + 3]), "r"(zero));
            wg_fence();
            wgmma_rs<B>(acc, a[0], a[1], a[2], a[3]);
            wg_commit();
        }
        wgmma_ss<1, (KC * 4 + 1) * 128, B + 2>(acc, cx.da0);
        wgmma_ss<1, (KC * 4 + 2) * 128, B + 4>(acc, cx.da0);
        wgmma_ss<1, (KC * 4 + 3) * 128, B + 6>(acc, cx.da0);
    }
    wg_commit();
    if (KC > 0) {
        wg_wait<1>();
        release<N - (KC > 0)>(cx);
    }
}

__host__ __device__ constexpr int sched_n(int t) { int v = SCHED; for (int i = t; i < 4; i++) v /= 10; return v % 10; }
__host__ __device__ constexpr int sched_sent(int t, int pos) {
    int c = 0;
    for (int i = 1; i < t; i++) c += sched_n(i);
    for (int k = 0; t <= 4 && k < sched_n(t); k++) c += k * 6 / sched_n(t) < pos;
    return c;
}
__host__ __device__ constexpr bool sched_ok() {
    for (int t = 1; t <= 4; t++) if (sched_n(t) > 6 || sched_sent(t + 1, 0) > 4 * t) return false;
    return sched_sent(5, 0) == 16;
}
static_assert(sched_ok(), "a piece is sent after its tile has been staged; only the last tile is left for the end");
__host__ __device__ constexpr int piece_off(int m) {
    return (m < 4 ? 8 + 4 * m : m < 12 ? m - 4 : 9 + (m - 12) / 3 * 4 + (m - 12) % 3) * 2048;
}
template <int V> struct IC { static constexpr int v = V; };

__device__ __forceinline__ int seg_row(int g) {
    const int y = g / 12;
    return y * (2 * HW) + (g - y * 12) * 32;
}

__device__ __forceinline__ bool tile_of(int i, int& j) {
    const int u = i / 5, t = i - u * 5;
    j = 4 * u + max(t - 1, 0);
    return t == 0;
}

template <int NP>
__global__ void __cluster_dims__(2, 1, 1) __launch_bounds__(NTHREADS, 1)
fpn_kernel(Scratch* scr, const __nv_bfloat16* __restrict__ c_ptr, const __nv_bfloat16* __restrict__ p_ptr,
           const int nsteps, const float one, const uint32_t zero,
           const __grid_constant__ CUtensorMap tm_wo, const __grid_constant__ CUtensorMap tm_wl3,
           const __grid_constant__ CUtensorMap tm_p8, const __grid_constant__ CUtensorMap tm_c,
           const __grid_constant__ CUtensorMap tm_p, const __grid_constant__ CUtensorMap tm_out,
           const __grid_constant__ CUtensorMap tm_cf)
{
    extern __shared__ __align__(1024) uint8_t smem[];
    const uint32_t sbase = smem_u32(smem);
    const int tid   = threadIdx.x;
    const int warp  = __shfl_sync(0xffffffffu, tid >> 5, 0);
    const int lane  = tid & 31;
    const int rank  = blockIdx.x & 1;
    const int pair  = blockIdx.x >> 1;
    const int npair = NP ? NP : gridDim.x >> 1;
    const int nfine = NP ? NSEG / (NP ? NP : 1) : nsteps;

    if (tid == 480) {
        prefetch_tmap(&tm_wo); prefetch_tmap(&tm_wl3); prefetch_tmap(&tm_p8);
        prefetch_tmap(&tm_c); prefetch_tmap(&tm_p); prefetch_tmap(&tm_out); prefetch_tmap(&tm_cf);
    }
    if (warp == 12 && elect_one()) {
        for (int s = 0; s < 3; s++) mbar_init(sbase + OFF_FULL + s * 8, 1);
        asm volatile("fence.mbarrier_init.release.cluster;" ::: "memory");
        asm volatile("fence.proxy.async.shared::cta;" ::: "memory");
        const int g0 = pair % 3;
#pragma unroll 1
        for (int s = 0; s < 3; s++) {
            const uint32_t bar = sbase + OFF_FULL + s * 8;
            const uint32_t dst = sbase + OFF_WOUT + g0 * WOUT_SLICE + s * 16384;
            mbar_expect_tx(bar, pair < NJOBS ? 3 * SLOT_BYTES : 2 * SLOT_BYTES);
            tma_load_2d(dst, &tm_wo, rank * 192 + g0 * 64, s * 128, bar);
            if (pair < NJOBS) tma_load_3d(sbase + OFF_RING + s * SLOT_BYTES, &tm_wl3, 0, (pair / 3) * 32, 2 * s, bar);
        }
    }
    if (warp == 13) {
        if (lane == 0) {
            for (int s = 0; s < NSLOTS; s++) {
                if (s >= 3) mbar_init(sbase + OFF_FULL + s * 8, 1);
                mbar_init(sbase + OFF_EMPTY + s * 8, 6);
            }
            mbar_init(sbase + OFF_JB2, 1);
            mbar_init(sbase + OFF_NB, 1);
            asm volatile("st.volatile.shared.u32 [%0], %1;" ::"r"(sbase + OFF_PACE), "r"(6) : "memory");
            asm volatile("fence.mbarrier_init.release.cluster;" ::: "memory");
            asm volatile("fence.proxy.async.shared::cta;" ::: "memory");
        }
        __syncwarp();
        asm volatile("bar.arrive 5, 448;" ::: "memory");
    }
    __syncwarp();
    asm volatile("barrier.cluster.arrive.relaxed.aligned;" ::: "memory");

    if (warp < 12) {
        uint32_t par;
        asm volatile("ld.relaxed.gpu.global.u32 %0, [%1];" : "=r"(par) : "l"(&scr->epoch) : "memory");
        asm volatile("setmaxnreg.inc.sync.aligned.u32 160;");
        asm volatile("bar.sync 5, 448;" ::: "memory");
        asm volatile("barrier.cluster.wait.aligned;" ::: "memory");
        const int wg   = warp >> 2;
        const int wtid = tid & 127;
        Ctx cx;
        cx.sbase     = sbase;
        cx.empty_tgt = mapa(sbase + OFF_EMPTY, warp & 1);
        cx.signal    = (lane == 0) && ((warp & 3) < 2);
        cx.da0       = desc_lo(sbase + OFF_WOUT + wg * WOUT_SLICE);
        const int cb = rank * 3 + wg;

        float    acc[32];
        uint32_t qp[16];
        uint32_t W[96];

        {
            uint32_t jph = 0;
            for (int job = pair; job < NJOBS; job += npair) {
                if (job % 3 == wg) {
                    if (job != pair) {
                        named_bar(wg);
                        if (wtid == 0) {
                            mbar_expect_tx(sbase + OFF_JB2, 6 * 4096);
                            for (int s = 0; s < 3; s++)
                                tma_load_3d(sbase + OFF_RING + s * SLOT_BYTES, &tm_wl3, 0, (job / 3) * 32, 2 * s, sbase + OFF_JB2);
                        }
                        for (int kc = 0; kc < 6; kc++) mbar_wait(sbase + OFF_FULL + (3 + kc) * 8, 0);
                        mbar_wait(sbase + OFF_JB2, jph);
                    }
                    float ja[16];
#define JOBK(k) wgmma_ss32<((k) > 0), (k) * 128, ((k) >> 2) * 256 + ((k) & 3) * 2>(ja, cx.da0);
                    mbar_wait(sbase + OFF_FULL, 0);
                    wg_fence();
                    JOBK(0)  JOBK(1)  JOBK(2)  JOBK(3)  JOBK(4)  JOBK(5)  JOBK(6)  JOBK(7)
                    wg_commit();
                    mbar_wait(sbase + OFF_FULL + 8, 0);
                    wg_fence();
                    JOBK(8)  JOBK(9)  JOBK(10) JOBK(11) JOBK(12) JOBK(13) JOBK(14) JOBK(15)
                    wg_commit();
                    mbar_wait(sbase + OFF_FULL + 16, 0);
                    wg_fence();
                    JOBK(16) JOBK(17) JOBK(18) JOBK(19) JOBK(20) JOBK(21) JOBK(22) JOBK(23)
#undef JOBK
                    wg_commit();
                    wg_wait<0>();
                    const int fidx = (cb * NFRAG + (job / 3) * 2) * 128 + wtid;
                    uint4* dst = scr->wfrag + (par & 1) * (6 * NFRAG * 128) + fidx;
#pragma unroll
                    for (int i = 0; i < 2; i++) {
                        asm volatile("st.relaxed.gpu.global.v4.u32 [%0], {%1, %2, %3, %4};" ::"l"(dst + i * 128),
                                     "r"(pack_neg(ja[8 * i + 0], ja[8 * i + 1])), "r"(pack_neg(ja[8 * i + 2], ja[8 * i + 3])),
                                     "r"(pack_neg(ja[8 * i + 4], ja[8 * i + 5])), "r"(pack_neg(ja[8 * i + 6], ja[8 * i + 7])) : "memory");
                    }
                }
                if (job + npair < NJOBS) asm volatile("bar.sync 4, 384;" ::: "memory");
                if (job != pair) jph ^= 1;
            }
        }

        par &= 1;
        mbar_wait(sbase + OFF_FULL, 0);
        mbar_wait(sbase + OFF_FULL + 8, 0);
        mbar_wait(sbase + OFF_FULL + 16, 0);
        asm volatile("bar.sync 6, 384;" ::: "memory");
        if (cx.signal) {
            mbar_arrive_cluster(cx.empty_tgt);
            mbar_arrive_cluster(cx.empty_tgt + 8);
            mbar_arrive_cluster(cx.empty_tgt + 16);
        }
        auto pack_q = [&]() {
            uint32_t all = 0;
#pragma unroll
            for (int i = 0; i < 16; i++) {
                qp[i] = pack_bf16(acc[2 * i], acc[2 * i + 1]);
                if (i >= 4) all |= qp[i];
            }
            qp[3] |= all & zero;
        };
        bool ready = false;
        uint32_t pu = 0;
#define CHUNK(N, MODE) chunk<N, MODE, false>(acc, W, qp, zero, cx, pu, ready, wg)

        const uint4* wsrc = scr->wfrag + (par * 6 + cb) * (NFRAG * 128) + wtid;
        auto load_w = [&](int kc) {
#pragma unroll
            for (int s = 4 * kc; s < 4 * kc + 4; s++) {
                asm volatile("ld.relaxed.gpu.global.v4.u32 {%0, %1, %2, %3}, [%4];"
                             : "=r"(W[4 * s]), "=r"(W[4 * s + 1]), "=r"(W[4 * s + 2]), "=r"(W[4 * s + 3])
                             : "l"(wsrc + s * 128) : "memory");
            }
        };
        auto check_w = [&](int kc) {
            uint32_t* w = kc < 6 ? W + 16 * kc : qp;
            asm volatile(
                "{\n.reg .pred p, q;\n.reg .u32 m, n;\n"
                "mov.u32 n, %17;\n"
                "CHK_%=:\n"
                "setp.ne.u32 q, n, 0;\n"
                "@q ld.relaxed.gpu.global.v4.u32 {%0, %1, %2, %3}, [%16];\n"
                "@q ld.relaxed.gpu.global.v4.u32 {%4, %5, %6, %7}, [%16 + 2048];\n"
                "@q ld.relaxed.gpu.global.v4.u32 {%8, %9, %10, %11}, [%16 + 4096];\n"
                "@q ld.relaxed.gpu.global.v4.u32 {%12, %13, %14, %15}, [%16 + 6144];\n"
                "min.u32 m, %0, %1;\n min.u32 m, m, %2;\n min.u32 m, m, %3;\n min.u32 m, m, %4;\n min.u32 m, m, %5;\n"
                "min.u32 m, m, %6;\n min.u32 m, m, %7;\n min.u32 m, m, %8;\n min.u32 m, m, %9;\n min.u32 m, m, %10;\n"
                "min.u32 m, m, %11;\n min.u32 m, m, %12;\n min.u32 m, m, %13;\n min.u32 m, m, %14;\n min.u32 m, m, %15;\n"
                "add.u32 n, n, 1;\n"
                "setp.eq.u32 p, m, 0;\n"
                "setp.lt.and.u32 p, n, 5000000, p;\n"
                "vote.sync.any.pred p, p, 0xffffffff;\n"
                "@p bra.uni CHK_%=;\n}"
                : "+r"(w[0]), "+r"(w[1]), "+r"(w[2]), "+r"(w[3]), "+r"(w[4]), "+r"(w[5]), "+r"(w[6]), "+r"(w[7]),
                  "+r"(w[8]), "+r"(w[9]), "+r"(w[10]), "+r"(w[11]), "+r"(w[12]), "+r"(w[13]), "+r"(w[14]), "+r"(w[15])
                : "l"(wsrc + kc * 512), "r"(zero) : "memory");
        };
        const uint32_t stage = sbase + OFF_WOUT + wg * WOUT_SLICE + 2 * 8192;
        const uint32_t st_addr = stage + (((lane >> 4) * 8 + (lane & 7)) << 7)
                               + (((((warp & 3) << 1) | ((lane >> 3) & 1)) ^ (lane & 7)) << 4);
        auto publish = [&](int s) {
            if (pair == (NJOBS + s) % npair) {
                uint32_t a[4];
                asm volatile("ldmatrix.sync.aligned.m8n8.x4.trans.shared.b16 {%0, %1, %2, %3}, [%4];"
                             : "=r"(a[0]), "=r"(a[1]), "=r"(a[2]), "=r"(a[3]) : "r"(st_addr + s * 8192) : "memory");
                asm volatile("st.relaxed.gpu.global.v4.u32 [%0], {%1, %2, %3, %4};" ::"l"(wsrc + (24 + s) * 128),
                             "r"(enc_neg(a[0])), "r"(enc_neg(a[1])), "r"(enc_neg(a[2])), "r"(enc_neg(a[3])) : "memory");
            }
        };
        CHUNK(0, COARSE);
        CHUNK(1, COARSE);
        CHUNK(2, COARSE);
        publish(0);
        load_w(0);
        CHUNK(3, COARSE);
        publish(1);
        load_w(1);
        CHUNK(4, COARSE);
        publish(2);
        load_w(2);
        CHUNK(5, COARSE);
        publish(3);
        wg_wait<0>();
        release<5>(cx);
        pack_q();

        auto flush_part = [&](int row, int part, bool on = true) {
            if (part == 0) {
                asm volatile("fence.proxy.async.shared::cta;" ::: "memory");
                named_bar(wg);
            }
            if (wtid == 0 && on) {
                tma_store_2d(&tm_out, cb * 64, row + (part >> 1) * HW + (part & 1) * 16, stage + part * 8192, POLICY_EVICT_FIRST);
                if (part == 3) asm volatile("cp.async.bulk.commit_group;" ::: "memory");
            }
        };
        auto init_acc = [&](int t) {
#pragma unroll
            for (int b = 0; b < 2; b++) {
#pragma unroll
                for (int h = 0; h < 2; h++) {
                    const uint32_t q = qp[t * 4 + b * 2 + h];
                    const float lo = __uint_as_float(q << 16), hi = __uint_as_float(q & 0xffff0000u);
#pragma unroll
                    for (int dy = 0; dy < 2; dy++) {
                        acc[16 * dy + 8 * b + 2 * h]         = dy ? dup(lo, one) : lo;
                        acc[16 * dy + 8 * b + 2 * h + 1]     = dup(lo, one);
                        acc[16 * dy + 8 * b + 4 + 2 * h]     = dy ? dup(hi, one) : hi;
                        acc[16 * dy + 8 * b + 4 + 2 * h + 1] = dup(hi, one);
                    }
                }
            }
        };
        auto stage_tile = [&](int slot) {
            if (wtid == 0) asm volatile("cp.async.bulk.wait_group.read 0;" ::: "memory");
            named_bar(wg);
            wg_wait<0>();
            if (cx.signal) mbar_arrive_cluster(cx.empty_tgt + slot * 8);
#pragma unroll
            for (int i = 0; i < 8; i += 2) {
                stsm_x4_t(st_addr + i * 4096,
                          pack_bf16(acc[4 * i + 0], acc[4 * i + 1]), pack_bf16(acc[4 * i + 2], acc[4 * i + 3]),
                          pack_bf16(acc[4 * i + 4], acc[4 * i + 5]), pack_bf16(acc[4 * i + 6], acc[4 * i + 7]));
            }
        };

        auto load_wo = [&]() {
#pragma unroll
            for (int s = 0; s < 4; s++) {
                asm volatile("ld.global.ca.v4.u32 {%0, %1, %2, %3}, [%4];"
                             : "=r"(qp[4 * s]), "=r"(qp[4 * s + 1]), "=r"(qp[4 * s + 2]), "=r"(qp[4 * s + 3])
                             : "l"(wsrc + (24 + s) * 128) : "memory");
            }
        };

        init_acc(0);
        check_w(0);
        load_w(3);
        load_w(4);
        CHUNK(6, FINE);
        check_w(1);
        CHUNK(7, FINE);
        check_w(2);
        CHUNK(8, FINE);
        check_w(3);
        load_w(5);
        CHUNK(9, FINE);
        check_w(4);
        CHUNK(10, FINE);
        check_w(5);
        CHUNK(11, FINE);

        int seg = pair;
        int prow = seg_row(seg);
        while (true) {
            stage_tile(slot_of<11>());
            init_acc(1);
            CHUNK(12, FINE);
            flush_part(prow, 0);
            CHUNK(13, FINE);
            CHUNK(14, FINE);
            flush_part(prow, 1);
            CHUNK(15, FINE);
            flush_part(prow, 2);
            CHUNK(16, FINE);
            flush_part(prow, 3);
            CHUNK(17, FINE);
            seg += npair;
            prow = seg_row(seg);
            stage_tile(slot_of<17>());
            init_acc(2);
            CHUNK(18, FINE);
            flush_part(prow, 0);
            CHUNK(19, FINE);
            CHUNK(20, FINE);
            flush_part(prow, 1);
            CHUNK(21, FINE);
            flush_part(prow, 2);
            CHUNK(22, FINE);
            flush_part(prow, 3);
            CHUNK(23, FINE);
            seg += npair;
            prow = seg_row(seg);
            stage_tile(slot_of<23>());
            init_acc(3);
            CHUNK(24, FINE);
            flush_part(prow, 0);
            CHUNK(25, FINE);
            load_wo();
            CHUNK(26, FINE);
            flush_part(prow, 1);
            CHUNK(27, FINE);
            flush_part(prow, 2);
            CHUNK(28, FINE);
            flush_part(prow, 3);
            CHUNK(29, FINE);
            seg += npair;
            prow = seg_row(seg);
            const bool tail = seg + 5 * npair >= NSEG;
            stage_tile(slot_of<29>());
            CHUNK(30, COARSE);
            flush_part(prow, 0, !tail);
            CHUNK(31, COARSE);
            check_w(6);
            CHUNK(32, COARSE_REG);
            CHUNK(33, COARSE_REG);
            flush_part(prow, 1, !tail);
            CHUNK(34, COARSE_REG);
            CHUNK(35, COARSE_REG);
            if (tail) break;
            wg_wait<0>();
            release<35>(cx);
            pack_q();
            init_acc(0);
            CHUNK(36, FINE);
            flush_part(prow, 2);
            CHUNK(37, FINE);
            CHUNK(38, FINE);
            CHUNK(39, FINE);
            flush_part(prow, 3);
            CHUNK(40, FINE);
            CHUNK(41, FINE);
            seg += npair;
            prow = seg_row(seg);
            pu ^= 1;
        }
#undef CHUNK

        wg_wait<0>();
        release<35>(cx);
        pack_q();
        auto send = [&](auto mc) {
            constexpr int m = decltype(mc)::v, off = piece_off(m);
            if (m % 4 == 0 && m > 0) prow = seg_row(seg + (m / 4) * npair);
            if (wtid == 0)
                tma_store_2d(&tm_out, cb * 64, prow + (m / 2 % 2) * HW + (m % 2) * 16, stage - 16384 + off, POLICY_EVICT_FIRST);
        };
        auto after = [&](auto tc, auto pc) {
            constexpr int t = decltype(tc)::v, pos = decltype(pc)::v, m = sched_sent(t, pos), n = sched_sent(t, pos + 1) - m;
            if (pos == 0 && t > 1) {
                asm volatile("fence.proxy.async.shared::cta;" ::: "memory");
                named_bar(wg);
            }
            if (n > 0) send(IC<m>{});
        };
        auto stage_piece = [&](auto mc) {
            constexpr int off = piece_off(decltype(mc)::v), i = decltype(mc)::v % 4 * 8;
            stsm_x4_t(st_addr - 16384 + off, pack_bf16(acc[i + 0], acc[i + 1]), pack_bf16(acc[i + 2], acc[i + 3]),
                                             pack_bf16(acc[i + 4], acc[i + 5]), pack_bf16(acc[i + 6], acc[i + 7]));
        };
#define TCHUNK(T, K) chunk<30 + 6 * T + K, FINE, true>(acc, W, qp, zero, cx, pu, ready, wg); after(IC<T>{}, IC<K>{});
#define TAIL_TILE(T)                                                                                          \
        init_acc(T - 1);                                                                                      \
        TCHUNK(T, 0) TCHUNK(T, 1) TCHUNK(T, 2) TCHUNK(T, 3) TCHUNK(T, 4) TCHUNK(T, 5)                         \
        wg_wait<0>();                                                                                         \
        release<35 + 6 * T>(cx);                                                                              \
        stage_piece(IC<4 * T>{}); stage_piece(IC<4 * T + 1>{}); stage_piece(IC<4 * T + 2>{}); stage_piece(IC<4 * T + 3>{});
        TAIL_TILE(1) TAIL_TILE(2) TAIL_TILE(3) TAIL_TILE(4)
#undef TAIL_TILE
#undef TCHUNK
        after(IC<5>{}, IC<0>{});
        send(IC<16>{}); send(IC<17>{}); send(IC<18>{}); send(IC<19>{});
        if (wtid == 0) asm volatile("cp.async.bulk.commit_group;" ::: "memory");
        if (wtid == 0) asm volatile("cp.async.bulk.wait_group.read 0;" ::: "memory");
    } else {
        asm volatile("setmaxnreg.dec.sync.aligned.u32 32;");
        if (warp == 12) {
            asm volatile("bar.sync 5, 448;" ::: "memory");
            if (elect_one()) {
                const int g1 = (pair + 1) % 3, g2 = (pair + 2) % 3;
#pragma unroll 1
                for (int kc = 0; kc < 6; kc++) {
                    const uint32_t bar = sbase + OFF_FULL + (3 + kc) * 8;
                    mbar_expect_tx(bar, (kc & 1) ? SLOT_BYTES : 5 * SLOT_BYTES);
                    tma_load_5d(sbase + OFF_RING + (3 + kc) * SLOT_BYTES, &tm_p8, kc * 64, pair * 2, 0, bar);
                    if (!(kc & 1)) {
                        tma_load_2d(sbase + OFF_WOUT + g1 * WOUT_SLICE + kc * 8192, &tm_wo, rank * 192 + g1 * 64, kc * 64, bar);
                        tma_load_2d(sbase + OFF_WOUT + g2 * WOUT_SLICE + kc * 8192, &tm_wo, rank * 192 + g2 * 64, kc * 64, bar);
                    }
                }
            }
            __syncwarp();
        }
        asm volatile("barrier.cluster.wait.aligned;" ::: "memory");
        if (warp == 12) {
            if ((sbase & 0x3FFFFu) != SMEM_BASE) asm volatile("trap;");
            const uint32_t dst0 = sbase + OFF_RING + rank * 4096;
            uint32_t so = 9 * 8, ph = 1, step = 6;
            auto next_slot = [&]() {
                so += 8;
                if (so == NSLOTS * 8) { so = 0; ph ^= 1; }
            };
            unsigned mytiles = 0, seen = 0;
            auto look = [&]() {
                asm volatile("ld.relaxed.gpu.global.u32 %0, [%1];" : "=r"(seen) : "l"(&scr->prog) : "memory");
            };
            auto tile = [&](bool coarse, int coord, uint64_t pol, bool last) {
                if (rank == 0 && mytiles >= GOV_START) {
                    const unsigned need = mytiles * npair - 2 * max(GOV_TIGHT - (int)mytiles, 0);
                    unsigned spins = 0;
                    while (__any_sync(0xffffffffu, (int)(need - seen) > 0) && ++spins < 100000u) look();
                }
                mytiles++;
#pragma unroll
                for (int kc = 0; kc < 6; kc++) {
                    const uint32_t bar = sbase + OFF_FULL + so, dst = dst0 + so * (SLOT_BYTES / 8);
                    mbar_wait_bounded(sbase + OFF_EMPTY + so, ph);
                    step++;
                    if (elect_one()) {
                        mbar_expect_tx(bar, SLOT_BYTES);
                        if (coarse) tma_load_5d_mc(dst, &tm_p, kc * 64, pair * 2, coord, bar, pol);
                        else        tma_load_2d_mc(dst, &tm_c, kc * 64, coord, bar, pol);
                        asm volatile("st.volatile.shared.u32 [%0], %1;" ::"r"(sbase + OFF_PACE), "r"(step) : "memory");
                    }
                    if (kc == 0 && rank == 0 && lane == 0 && !last)
                        asm volatile("red.relaxed.gpu.global.add.u32 [%0], 1;" ::"l"(&scr->prog) : "memory");
                    next_slot();
                    if (kc == 3 && rank == 0) look();
                }
            };
            const int ntiles = nfine + nfine / 4;
#pragma unroll 1
            for (int i = 1; i < ntiles; i++) {
                int j;
                const bool coarse = tile_of(i, j);
                tile(coarse, coarse ? j + 2 * rank : seg_row(j * npair + pair) + rank * HW,
                     i >= ntiles - EF_TILES ? POLICY_EVICT_FIRST : POLICY_EVICT_NORMAL, i + 1 == ntiles);
            }
            if (rank == 0 && lane == 0) {
                if (atomicAdd(&scr->prog, 1u) + 1 == mytiles * npair) {
                    asm volatile("st.relaxed.gpu.global.u32 [%0], 0;" ::"l"(&scr->prog) : "memory");
                    asm volatile("red.relaxed.gpu.global.add.u32 [%0], 1;" ::"l"(&scr->epoch) : "memory");
                }
            }
            __syncwarp();
#pragma unroll 1
            for (int s = 0; s < NSLOTS; s++) {
                mbar_wait_bounded(sbase + OFF_EMPTY + so, ph);
                next_slot();
            }
        } else if (warp == 13) {
            auto wait_pace = [&](int need) {
                unsigned spins = 0;
                while (true) {
                    uint32_t v;
                    asm volatile("ld.volatile.shared.u32 %0, [%1];" : "=r"(v) : "r"(sbase + OFF_PACE) : "memory");
                    if ((int)v >= need || ++spins > 4000000u) break;
                    __nanosleep(20);
                }
            };
            if (lane == 0) mbar_expect_tx(sbase + OFF_NB, 12 * 512);
#pragma unroll 1
            for (int k = 0; k < 12; k++) {
                const int j = k < 6 ? 2 : 3;
                wait_pace(PF_FIRST + k * 3 / 4);
                if (lane == 0)
                    tma_load_2d(sbase + OFF_SINK, &tm_cf, 0, (seg_row(j * npair + pair) + rank * HW) * 6 + (k - (j - 2) * 6) * 32,
                                sbase + OFF_NB);
            }
#pragma unroll 1
            for (int i = 5; i < nfine + nfine / 4; i++) {
                int j;
                const char *b0, *b1;
                if (tile_of(i, j)) {
                    b0 = (const char*)p_ptr + (size_t)((j + 2 * rank) * npair + pair) * (16 * C * 2);
                    b1 = b0 + (size_t)npair * (16 * C * 2);
                } else {
                    b0 = (const char*)c_ptr + (size_t)(seg_row(j * npair + pair) + rank * HW) * (C * 2);
                    b1 = b0 + 16 * C * 2;
                }
                wait_pace(6 * i - max(PF_LEAD0 - max(i - PF_DECAY, 0), PF_LEAD));
#pragma unroll
                for (int k = 0; k < 6; k++) {
                    asm volatile("prefetch.global.L2 [%0];" ::"l"((k < 3 ? b0 : b1) + lane * 128 + (k % 3) * 4096) : "memory");
                    __nanosleep(PF_GAP);
                }
            }
            mbar_wait_bounded(sbase + OFF_NB, 0);
        } else if (warp == 15) {
            uint32_t par, v;
            asm volatile("ld.relaxed.gpu.global.u32 %0, [%1];" : "=r"(par) : "l"(&scr->epoch) : "memory");
            uint4* clr = scr->wfrag + (~par & 1) * (6 * NFRAG * 128);
            unsigned spins = 0;
            do {
                __nanosleep(500);
                asm volatile("ld.volatile.shared.u32 %0, [%1];" : "=r"(v) : "r"(sbase + OFF_PACE) : "memory");
            } while (v < CLR_AT && ++spins < 100000u);
#pragma unroll 1
            for (int i = blockIdx.x * 32 + lane; i < 6 * NFRAG * 128; i += npair * 64) clr[i] = make_uint4(0u, 0u, 0u, 0u);
        }
    }
}

typedef CUresult (*EncodeFn)(CUtensorMap*, CUtensorMapDataType, cuuint32_t, void*, const cuuint64_t*, const cuuint64_t*,
                             const cuuint32_t*, const cuuint32_t*, CUtensorMapInterleave, CUtensorMapSwizzle,
                             CUtensorMapL2promotion, CUtensorMapFloatOOBfill);

void encode(EncodeFn fn, CUtensorMap* tm, const void* ptr, int rank, const cuuint64_t* dims, const cuuint64_t* strides,
            const cuuint32_t* box, CUtensorMapSwizzle swizzle = CU_TENSOR_MAP_SWIZZLE_128B,
            CUtensorMapL2promotion promotion = CU_TENSOR_MAP_L2_PROMOTION_NONE) {
    const cuuint32_t es[5] = {1, 1, 1, 1, 1};
    fn(tm, CU_TENSOR_MAP_DATA_TYPE_BFLOAT16, (cuuint32_t)rank, const_cast<void*>(ptr), dims, strides, box, es,
       CU_TENSOR_MAP_INTERLEAVE_NONE, swizzle, promotion, CU_TENSOR_MAP_FLOAT_OOB_FILL_NONE);
}

}

extern "C" void kernel_launch(void* const* d_in, const int* in_sizes, int n_in, void* d_out, int out_size) {
    (void)in_sizes; (void)n_in; (void)out_size;
    const __nv_bfloat16* c_fine   = (const __nv_bfloat16*)d_in[0];
    const __nv_bfloat16* p_coarse = (const __nv_bfloat16*)d_in[1];
    const __nv_bfloat16* w_lat    = (const __nv_bfloat16*)d_in[2];
    const __nv_bfloat16* w_out    = (const __nv_bfloat16*)d_in[3];

    static EncodeFn fn = nullptr;
    static int np = 0;
    static Scratch* scr = nullptr;
    if (!fn) {
        void* p = nullptr;
        cudaDriverEntryPointQueryResult qr;
        cudaGetDriverEntryPoint("cuTensorMapEncodeTiled", &p, cudaEnableDefault, &qr);
        fn = (EncodeFn)p;
        cudaGetSymbolAddress((void**)&scr, g_scratch);
        cudaFuncSetAttribute(fpn_kernel<NPAIRS>, cudaFuncAttributeMaxDynamicSharedMemorySize, SMEM_BYTES);
        cudaFuncSetAttribute(fpn_kernel<0>, cudaFuncAttributeMaxDynamicSharedMemorySize, SMEM_BYTES);
        cudaLaunchConfig_t cfg = {};
        cfg.gridDim = dim3(2); cfg.blockDim = dim3(NTHREADS); cfg.dynamicSmemBytes = SMEM_BYTES;
        cudaLaunchAttribute at[1];
        at[0].id = cudaLaunchAttributeClusterDimension;
        at[0].val.clusterDim.x = 2; at[0].val.clusterDim.y = 1; at[0].val.clusterDim.z = 1;
        cfg.attrs = at; cfg.numAttrs = 1;
        if (cudaOccupancyMaxActiveClusters(&np, fpn_kernel<0>, &cfg) != cudaSuccess || np < 1) np = 1;
        if (np > NPAIRS) np = NPAIRS;
        while ((NSEG / 4) % np) np--;
    }

    CUtensorMap tm_cf, tm_c, tm_p, tm_wl3, tm_out, tm_p8, tm_wo;
    {
        const cuuint64_t dims[2] = {(cuuint64_t)C, (cuuint64_t)NPIX};
        const cuuint64_t str[1]  = {(cuuint64_t)C * 2};
        const cuuint32_t box_in[2]  = {64, 32};
        const cuuint32_t box_out[2] = {64, 16};
        encode(fn, &tm_c, c_fine, 2, dims, str, box_in);
        encode(fn, &tm_out, d_out, 2, dims, str, box_out);
    }
    {
        const cuuint64_t dims[5] = {(cuuint64_t)C, 2, 4, (cuuint64_t)(2 * np), (cuuint64_t)(NSEG / np)};
        const cuuint64_t str[4]  = {(cuuint64_t)4 * C * 2, (cuuint64_t)C * 2, (cuuint64_t)8 * C * 2, (cuuint64_t)np * 16 * C * 2};
        const cuuint32_t box[5]  = {64, 2, 4, 2, 2};
        encode(fn, &tm_p, p_coarse, 5, dims, str, box);
        const cuuint32_t box8[5] = {64, 2, 4, 2, 4};
        encode(fn, &tm_p8, p_coarse, 5, dims, str, box8);
    }
    {
        const cuuint64_t dims[2] = {(cuuint64_t)C, (cuuint64_t)C};
        const cuuint64_t str[1]  = {(cuuint64_t)C * 2};
        const cuuint32_t box[2] = {64, 128};
        encode(fn, &tm_wo, w_out, 2, dims, str, box);
    }
    {
        const cuuint64_t dims[3] = {64, (cuuint64_t)C, 6};
        const cuuint64_t str[2]  = {(cuuint64_t)C * 2, 128};
        const cuuint32_t box[3]  = {64, 32, 2};
        encode(fn, &tm_wl3, w_lat, 3, dims, str, box);
    }
    {
        const cuuint64_t dims[2] = {64, (cuuint64_t)NPIX * 6};
        const cuuint64_t str[1]  = {128};
        const cuuint32_t box[2]  = {8, 32};
        encode(fn, &tm_cf, c_fine, 2, dims, str, box, CU_TENSOR_MAP_SWIZZLE_NONE, CU_TENSOR_MAP_L2_PROMOTION_L2_128B);
    }
    auto kernel = np == NPAIRS ? fpn_kernel<NPAIRS> : fpn_kernel<0>;
    kernel<<<2 * np, NTHREADS, SMEM_BYTES>>>(scr, c_fine, p_coarse, NSEG / np, 1.0f, 0u,
                                             tm_wo, tm_wl3, tm_p8, tm_c, tm_p, tm_out, tm_cf);
}
```

```cpp
#include <cuda_runtime.h>
#include <cuda_bf16.h>
#include <cuda.h>
#include <stdint.h>

namespace {

constexpr int C          = 384;
constexpr int HW         = 384;
constexpr int NPIX       = HW * HW;
constexpr int NSEG       = NPIX / 64;
constexpr int NJOBS      = 36;

constexpr int NFRAG      = 28;
constexpr int NSLOTS     = 10;
constexpr int NPAIRS     = 64;
constexpr int PF_LEAD    = 5;
constexpr int PF_LEAD0   = 18;
constexpr int PF_DECAY   = 12;
constexpr int PF_FIRST   = 11;
constexpr int PF_GAP     = 50;
constexpr int GOV_START  = 12;
constexpr int GOV_TIGHT  = 26;
constexpr int EF_TILES   = 13;
constexpr int SCHED      = 2266;

constexpr int SLOT_BYTES  = 8192;
constexpr int WOUT_SLICE  = 384 * 128;
constexpr int OFF_WOUT    = 0;
constexpr int OFF_RING    = 3 * WOUT_SLICE;
constexpr int OFF_FULL    = OFF_RING + NSLOTS * SLOT_BYTES;
constexpr int OFF_EMPTY   = OFF_FULL + 8 * NSLOTS;
constexpr int OFF_JB2     = OFF_EMPTY + 8 * NSLOTS;
constexpr int OFF_PACE    = OFF_JB2 + 8;
constexpr int OFF_NB      = OFF_PACE + 8;
constexpr int OFF_SINK    = (OFF_NB + 8 + 127) / 128 * 128;
constexpr int SMEM_BYTES  = OFF_SINK + 512;
static_assert(SMEM_BYTES <= 232448, "smem");
static_assert(NSLOTS == 10, "a unit (30 ring items) must be an odd number of rounds of the ring");

constexpr int      SMEM_BASE = 1024;
constexpr uint64_t DESC_RING = 0x4000004000010000ull + ((SMEM_BASE + OFF_RING) >> 4);

constexpr int NTHREADS = 512;
constexpr uint64_t POLICY_EVICT_FIRST  = 0x12F0000000000000ull;
constexpr uint64_t POLICY_EVICT_NORMAL = 0x1000000000000000ull;

struct Scratch {
    uint4    wfrag[2 * 6 * NFRAG * 128];
    unsigned epoch;
    unsigned pad0[31];
    unsigned prog;
};
__device__ Scratch g_scratch;

__device__ __forceinline__ uint32_t smem_u32(const void* p) { return (uint32_t)__cvta_generic_to_shared(p); }

__device__ __forceinline__ void mbar_init(uint32_t bar, uint32_t cnt) {
    asm volatile("mbarrier.init.shared::cta.b64 [%0], %1;" ::"r"(bar), "r"(cnt) : "memory");
}
__device__ __forceinline__ void mbar_expect_tx(uint32_t bar, uint32_t bytes) {
    asm volatile("mbarrier.arrive.expect_tx.shared::cta.b64 _, [%0], %1;" ::"r"(bar), "r"(bytes) : "memory");
}
__device__ __forceinline__ void mbar_wait_bounded(uint32_t bar, uint32_t parity) {
    asm volatile(
        "{\n"
        ".reg .pred p;\n"
        ".reg .u32 n;\n"
        "mbarrier.try_wait.parity.shared::cta.b64 p, [%0], %1;\n"
        "@p bra DONE_%=;\n"
        "mov.u32 n, 0;\n"
        "WAIT_%=:\n"
        "mbarrier.try_wait.parity.shared::cta.b64 p, [%0], %1;\n"
        "@p bra DONE_%=;\n"
        "add.u32 n, n, 1;\n"
        "setp.lt.u32 p, n, 4000000;\n"
        "@p bra WAIT_%=;\n"
        "trap;\n"
        "DONE_%=:\n"
        "}\n" ::"r"(bar), "r"(parity) : "memory");
}
__device__ __forceinline__ void mbar_wait(uint32_t bar, uint32_t parity) {
    asm volatile(
        "{\n"
        ".reg .pred p;\n"
        "WAIT_%=:\n"
        "mbarrier.try_wait.parity.shared::cta.b64 p, [%0], %1;\n"
        "@!p bra WAIT_%=;\n"
        "}\n" ::"r"(bar), "r"(parity) : "memory");
}
__device__ __forceinline__ bool mbar_try(uint32_t bar, uint32_t parity) {
    uint32_t r;
    asm volatile("{\n.reg .pred p;\nmbarrier.test_wait.parity.shared::cta.b64 p, [%1], %2;\nselp.u32 %0, 1, 0, p;\n}\n"
                 : "=r"(r) : "r"(bar), "r"(parity) : "memory");
    return r != 0;
}
__device__ __forceinline__ void mbar_arrive_cluster(uint32_t cluster_addr) {
    asm volatile("mbarrier.arrive.shared::cluster.b64 _, [%0];" ::"r"(cluster_addr) : "memory");
}
__device__ __forceinline__ uint32_t mapa(uint32_t addr, uint32_t rank) {
    uint32_t r;
    asm("mapa.shared::cluster.u32 %0, %1, %2;" : "=r"(r) : "r"(addr), "r"(rank));
    return r;
}
__device__ __forceinline__ void named_bar(int wg) {
    asm volatile("bar.sync %0, 128;" ::"r"(wg + 1) : "memory");
}

__device__ __forceinline__ void tma_load_2d(uint32_t dst, const CUtensorMap* tm, int c0, int c1, uint32_t bar) {
    asm volatile("cp.async.bulk.tensor.2d.shared::cluster.global.mbarrier::complete_tx::bytes [%0], [%1, {%2, %3}], [%4];"
                 ::"r"(dst), "l"(tm), "r"(c0), "r"(c1), "r"(bar) : "memory");
}
__device__ __forceinline__ void tma_load_3d(uint32_t dst, const CUtensorMap* tm, int c0, int c1, int c2, uint32_t bar) {
    asm volatile("cp.async.bulk.tensor.3d.shared::cluster.global.mbarrier::complete_tx::bytes [%0], [%1, {%2, %3, %4}], [%5];"
                 ::"r"(dst), "l"(tm), "r"(c0), "r"(c1), "r"(c2), "r"(bar) : "memory");
}
__device__ __forceinline__ void tma_load_5d(uint32_t dst, const CUtensorMap* tm, int c0, int c3, int c4, uint32_t bar) {
    asm volatile("cp.async.bulk.tensor.5d.shared::cluster.global.mbarrier::complete_tx::bytes [%0], [%1, {%2, 0, 0, %3, %4}], [%5];"
                 ::"r"(dst), "l"(tm), "r"(c0), "r"(c3), "r"(c4), "r"(bar) : "memory");
}
__device__ __forceinline__ void tma_load_2d_mc(uint32_t dst, const CUtensorMap* tm, int c0, int c1, uint32_t bar, uint64_t pol) {
    asm volatile("cp.async.bulk.tensor.2d.shared::cluster.global.mbarrier::complete_tx::bytes.multicast::cluster.L2::cache_hint"
                 " [%0], [%1, {%2, %3}], [%4], %5, %6;"
                 ::"r"(dst), "l"(tm), "r"(c0), "r"(c1), "r"(bar), "h"((uint16_t)3), "l"(pol) : "memory");
}
__device__ __forceinline__ void tma_load_5d_mc(uint32_t dst, const CUtensorMap* tm, int c0, int c3, int c4, uint32_t bar, uint64_t pol) {
    asm volatile("cp.async.bulk.tensor.5d.shared::cluster.global.mbarrier::complete_tx::bytes.multicast::cluster.L2::cache_hint"
                 " [%0], [%1, {%2, 0, 0, %3, %4}], [%5], %6, %7;"
                 ::"r"(dst), "l"(tm), "r"(c0), "r"(c3), "r"(c4), "r"(bar), "h"((uint16_t)3), "l"(pol) : "memory");
}
__device__ __forceinline__ void tma_store_2d(const CUtensorMap* tm, int c0, int c1, uint32_t src, uint64_t pol) {
    asm volatile("cp.async.bulk.tensor.2d.global.shared::cta.bulk_group.L2::cache_hint [%0, {%1, %2}], [%3], %4;"
                 ::"l"(tm), "r"(c0), "r"(c1), "r"(src), "l"(pol) : "memory");
}
__device__ __forceinline__ bool elect_one() {
    uint32_t r;
    asm volatile("{\n.reg .pred p;\nelect.sync _|p, 0xffffffff;\nselp.u32 %0, 1, 0, p;\n}" : "=r"(r));
    return r != 0;
}
__device__ __forceinline__ void prefetch_tmap(const CUtensorMap* tm) {
    asm volatile("prefetch.tensormap [%0];" ::"l"(tm) : "memory");
}

__device__ __forceinline__ void wg_fence()  { asm volatile("wgmma.fence.sync.aligned;" ::: "memory"); }
__device__ __forceinline__ void wg_commit() { asm volatile("wgmma.commit_group.sync.aligned;" ::: "memory"); }
template <int N> __device__ __forceinline__ void wg_wait() { asm volatile("wgmma.wait_group.sync.aligned %0;" ::"n"(N) : "memory"); }

#define ACC16(a)                                                                                              \
    "+f"(a[0]), "+f"(a[1]), "+f"(a[2]), "+f"(a[3]), "+f"(a[4]), "+f"(a[5]), "+f"(a[6]), "+f"(a[7]),           \
    "+f"(a[8]), "+f"(a[9]), "+f"(a[10]), "+f"(a[11]), "+f"(a[12]), "+f"(a[13]), "+f"(a[14]), "+f"(a[15])
#define ACC32(a)                                                                                              \
    ACC16(a),                                                                                                 \
    "+f"(a[16]), "+f"(a[17]), "+f"(a[18]), "+f"(a[19]), "+f"(a[20]), "+f"(a[21]), "+f"(a[22]), "+f"(a[23]),   \
    "+f"(a[24]), "+f"(a[25]), "+f"(a[26]), "+f"(a[27]), "+f"(a[28]), "+f"(a[29]), "+f"(a[30]), "+f"(a[31])
#define ACC16_STR "{%0, %1, %2, %3, %4, %5, %6, %7, %8, %9, %10, %11, %12, %13, %14, %15}"
#define ACC32_STR                                                                                             \
    "{%0, %1, %2, %3, %4, %5, %6, %7, %8, %9, %10, %11, %12, %13, %14, %15, "                                 \
    "%16, %17, %18, %19, %20, %21, %22, %23, %24, %25, %26, %27, %28, %29, %30, %31}"

template <int BOFF>
__device__ __forceinline__ void wgmma_rs(float (&d)[32], uint32_t a0, uint32_t a1, uint32_t a2, uint32_t a3) {
    asm volatile("{\n.reg .b64 db;\n"
                 "mov.b64 db, %36;\n"
                 "wgmma.mma_async.sync.aligned.m64n64k16.f32.bf16.bf16 " ACC32_STR
                 ", {%32, %33, %34, %35}, db, 1, -1, 1, 0;\n}"
                 : ACC32(d) : "r"(a0), "r"(a1), "r"(a2), "r"(a3), "n"(DESC_RING + BOFF));
}
template <int ACCUM, int AOFF, int BOFF>
__device__ __forceinline__ void wgmma_ss(float (&d)[32], uint32_t da_lo) {
    asm volatile("{\n.reg .b64 da, db;\n.reg .b32 lo;\n"
                 "add.u32 lo, %32, %34;\nmov.b64 da, {lo, 0x40000040};\n"
                 "mov.b64 db, %35;\n"
                 "wgmma.mma_async.sync.aligned.m64n64k16.f32.bf16.bf16 " ACC32_STR
                 ", da, db, %33, 1, 1, 1, 0;\n}"
                 : ACC32(d) : "r"(da_lo), "n"(ACCUM), "n"(AOFF), "n"(DESC_RING + BOFF));
}
template <int ACCUM, int AOFF, int BOFF>
__device__ __forceinline__ void wgmma_ss32(float (&d)[16], uint32_t da_lo) {
    asm volatile("{\n.reg .b64 da, db;\n.reg .b32 lo;\n"
                 "add.u32 lo, %16, %18;\nmov.b64 da, {lo, 0x40000040};\n"
                 "mov.b64 db, %19;\n"
                 "wgmma.mma_async.sync.aligned.m64n32k16.f32.bf16.bf16 " ACC16_STR
                 ", da, db, %17, 1, 1, 1, 0;\n}"
                 : ACC16(d) : "r"(da_lo), "n"(ACCUM), "n"(AOFF), "n"(DESC_RING + BOFF));
}
__device__ __forceinline__ uint32_t desc_lo(uint32_t addr) { return ((addr & 0x3FFFFu) >> 4) | (1u << 16); }
__device__ __forceinline__ uint32_t pack_bf16(float lo, float hi) {
    uint32_t r;
    asm("cvt.rn.bf16x2.f32 %0, %1, %2;" : "=r"(r) : "f"(hi), "f"(lo));
    return r;
}
__device__ __forceinline__ uint32_t enc_neg(uint32_t pair) {
    const uint32_t v = pair ^ 0x80008000u;
    return v == 0u ? 0x80008000u : v;
}
__device__ __forceinline__ uint32_t pack_neg(float lo, float hi) { return enc_neg(pack_bf16(lo, hi)); }
__device__ __forceinline__ float dup(float x, float one) {
    float r;
    asm volatile("mul.f32 %0, %1, %2;" : "=f"(r) : "f"(x), "f"(one));
    return r;
}
__device__ __forceinline__ void stsm_x4_t(uint32_t addr, uint32_t r0, uint32_t r1, uint32_t r2, uint32_t r3) {
    asm volatile("stmatrix.sync.aligned.m8n8.x4.trans.shared.b16 [%0], {%1, %2, %3, %4};"
                 ::"r"(addr), "r"(r0), "r"(r1), "r"(r2), "r"(r3) : "memory");
}

struct Ctx {
    uint32_t sbase;
    uint32_t da0;
    uint32_t empty_tgt;
    bool     signal;
};

template <int N> __device__ __forceinline__ constexpr uint32_t slot_of() { return (3 + N) % NSLOTS; }
template <int N> __device__ __forceinline__ uint32_t phase_of(uint32_t pu) { return pu ^ (((3 + N) / NSLOTS) & 1); }
template <int N> __device__ __forceinline__ void release(const Ctx& cx) {
    if (cx.signal) mbar_arrive_cluster(cx.empty_tgt + slot_of<N>() * 8);
}

enum { FINE, COARSE, COARSE_REG };
template <int N, int MODE, bool SKEW>
__device__ __forceinline__ void chunk(float (&acc)[32], const uint32_t (&W)[96], const uint32_t (&A)[16], uint32_t zero,
                                      const Ctx& cx, uint32_t pu, bool& ready, int wg) {
    constexpr int KC = N % 6;
    constexpr int B  = slot_of<N>() * 512;
    if (!ready) mbar_wait(cx.sbase + OFF_FULL + slot_of<N>() * 8, phase_of<N>(pu));
    ready = mbar_try(cx.sbase + OFF_FULL + slot_of<N + 1>() * 8, phase_of<N + 1>(pu));
    if (SKEW) {
        const int id = 8 + ((N / 6) & 1) * 4 + wg;
        if (KC == 2 && wg > 0) asm volatile("bar.sync %0, 256;" ::"r"(id - 1) : "memory");
        if (KC == 4 && wg < 2) asm volatile("bar.arrive %0, 256;" ::"r"(id) : "memory");
    }
    if (MODE == FINE) {
        wg_fence();
        wgmma_rs<B + 0>(acc, W[KC * 16 + 0],  W[KC * 16 + 1],  W[KC * 16 + 2],  W[KC * 16 + 3]);
        wgmma_rs<B + 2>(acc, W[KC * 16 + 4],  W[KC * 16 + 5],  W[KC * 16 + 6],  W[KC * 16 + 7]);
        wgmma_rs<B + 4>(acc, W[KC * 16 + 8],  W[KC * 16 + 9],  W[KC * 16 + 10], W[KC * 16 + 11]);
        wgmma_rs<B + 6>(acc, W[KC * 16 + 12], W[KC * 16 + 13], W[KC * 16 + 14], W[KC * 16 + 15]);
    } else {
        if (MODE == COARSE) {
            wg_fence();
            wgmma_ss<(KC > 0), KC * 4 * 128, B>(acc, cx.da0);
        } else {
            uint32_t a[4];
            asm volatile("{\n.reg .u32 z;\nmov.u32 z, %%clock;\nand.b32 z, z, %8;\n"
                         "xor.b32 %0, %4, z;\nxor.b32 %1, %5, z;\nxor.b32 %2, %6, z;\nxor.b32 %3, %7, z;\n}"
                         : "=r"(a[0]), "=r"(a[1]), "=r"(a[2]), "=r"(a[3])
                         : "r"(A[((KC + 2) & 3) * 4]), "r"(A[((KC + 2) & 3) * 4 + 1]), "r"(A[((KC + 2) & 3) * 4 + 2]),
                           "r"(A[((KC + 2) & 3) * 4 + 3]), "r"(zero));
            wg_fence();
            wgmma_rs<B>(acc, a[0], a[1], a[2], a[3]);
            wg_commit();
        }
        wgmma_ss<1, (KC * 4 + 1) * 128, B + 2>(acc, cx.da0);
        wgmma_ss<1, (KC * 4 + 2) * 128, B + 4>(acc, cx.da0);
        wgmma_ss<1, (KC * 4 + 3) * 128, B + 6>(acc, cx.da0);
    }
    wg_commit();
    if (KC > 0) {
        wg_wait<1>();
        release<N - (KC > 0)>(cx);
    }
}

__host__ __device__ constexpr int sched_n(int t) { int v = SCHED; for (int i = t; i < 4; i++) v /= 10; return v % 10; }
__host__ __device__ constexpr int sched_sent(int t, int pos) {
    int c = 0;
    for (int i = 1; i < t; i++) c += sched_n(i);
    for (int k = 0; t <= 4 && k < sched_n(t); k++) c += k * 6 / sched_n(t) < pos;
    return c;
}
__host__ __device__ constexpr bool sched_ok() {
    for (int t = 1; t <= 4; t++) if (sched_n(t) > 6 || sched_sent(t + 1, 0) > 4 * t) return false;
    return sched_sent(5, 0) == 16;
}
static_assert(sched_ok(), "a piece is sent after its tile has been staged; only the last tile is left for the end");
__host__ __device__ constexpr int piece_off(int m) {
    return (m < 4 ? 8 + 4 * m : m < 12 ? m - 4 : 9 + (m - 12) / 3 * 4 + (m - 12) % 3) * 2048;
}
template <int V> struct IC { static constexpr int v = V; };

__device__ __forceinline__ int seg_row(int g) {
    const int y = g / 12;
    return y * (2 * HW) + (g - y * 12) * 32;
}

__device__ __forceinline__ bool tile_of(int i, int& j) {
    const int u = i / 5, t = i - u * 5;
    j = 4 * u + max(t - 1, 0);
    return t == 0;
}

template <int NP>
__global__ void __cluster_dims__(2, 1, 1) __launch_bounds__(NTHREADS, 1)
fpn_kernel(Scratch* scr, const __nv_bfloat16* __restrict__ c_ptr, const __nv_bfloat16* __restrict__ p_ptr,
           const int nsteps, const float one, const uint32_t zero,
           const __grid_constant__ CUtensorMap tm_wo, const __grid_constant__ CUtensorMap tm_wl3,
           const __grid_constant__ CUtensorMap tm_p8, const __grid_constant__ CUtensorMap tm_c,
           const __grid_constant__ CUtensorMap tm_p, const __grid_constant__ CUtensorMap tm_out,
           const __grid_constant__ CUtensorMap tm_cf)
{
    extern __shared__ __align__(1024) uint8_t smem[];
    const uint32_t sbase = smem_u32(smem);
    const int tid   = threadIdx.x;
    const int warp  = __shfl_sync(0xffffffffu, tid >> 5, 0);
    const int lane  = tid & 31;
    const int rank  = blockIdx.x & 1;
    const int pair  = blockIdx.x >> 1;
    const int npair = NP ? NP : gridDim.x >> 1;
    const int nfine = NP ? NSEG / (NP ? NP : 1) : nsteps;

    if (tid == 480) {
        prefetch_tmap(&tm_wo); prefetch_tmap(&tm_wl3); prefetch_tmap(&tm_p8);
        prefetch_tmap(&tm_c); prefetch_tmap(&tm_p); prefetch_tmap(&tm_out); prefetch_tmap(&tm_cf);
    }
    if (warp == 12 && elect_one()) {
        for (int s = 0; s < 3; s++) mbar_init(sbase + OFF_FULL + s * 8, 1);
        asm volatile("fence.mbarrier_init.release.cluster;" ::: "memory");
        asm volatile("fence.proxy.async.shared::cta;" ::: "memory");
        const int g0 = pair % 3;
#pragma unroll 1
        for (int s = 0; s < 3; s++) {
            const uint32_t bar = sbase + OFF_FULL + s * 8;
            const uint32_t dst = sbase + OFF_WOUT + g0 * WOUT_SLICE + s * 16384;
            mbar_expect_tx(bar, pair < NJOBS ? 3 * SLOT_BYTES : 2 * SLOT_BYTES);
            tma_load_2d(dst, &tm_wo, rank * 192 + g0 * 64, s * 128, bar);
            if (pair < NJOBS) tma_load_3d(sbase + OFF_RING + s * SLOT_BYTES, &tm_wl3, 0, (pair / 3) * 32, 2 * s, bar);
        }
    }
    if (warp == 13) {
        if (lane == 0) {
            for (int s = 0; s < NSLOTS; s++) {
                if (s >= 3) mbar_init(sbase + OFF_FULL + s * 8, 1);
                mbar_init(sbase + OFF_EMPTY + s * 8, 6);
            }
            mbar_init(sbase + OFF_JB2, 1);
            mbar_init(sbase + OFF_NB, 1);
            asm volatile("st.volatile.shared.u32 [%0], %1;" ::"r"(sbase + OFF_PACE), "r"(6) : "memory");
            asm volatile("fence.mbarrier_init.release.cluster;" ::: "memory");
            asm volatile("fence.proxy.async.shared::cta;" ::: "memory");
        }
        __syncwarp();
        asm volatile("bar.arrive 5, 448;" ::: "memory");
    }
    __syncwarp();
    asm volatile("barrier.cluster.arrive.relaxed.aligned;" ::: "memory");

    if (warp < 12) {
        uint32_t par;
        asm volatile("ld.relaxed.gpu.global.u32 %0, [%1];" : "=r"(par) : "l"(&scr->epoch) : "memory");
        asm volatile("setmaxnreg.inc.sync.aligned.u32 160;");
        asm volatile("bar.sync 5, 448;" ::: "memory");
        asm volatile("barrier.cluster.wait.aligned;" ::: "memory");
        const int wg   = warp >> 2;
        const int wtid = tid & 127;
        Ctx cx;
        cx.sbase     = sbase;
        cx.empty_tgt = mapa(sbase + OFF_EMPTY, warp & 1);
        cx.signal    = (lane == 0) && ((warp & 3) < 2);
        cx.da0       = desc_lo(sbase + OFF_WOUT + wg * WOUT_SLICE);
        const int cb = rank * 3 + wg;

        float    acc[32];
        uint32_t qp[16];
        uint32_t W[96];

        {
            uint32_t jph = 0;
            for (int job = pair; job < NJOBS; job += npair) {
                if (job % 3 == wg) {
                    if (job != pair) {
                        named_bar(wg);
                        if (wtid == 0) {
                            mbar_expect_tx(sbase + OFF_JB2, 6 * 4096);
                            for (int s = 0; s < 3; s++)
                                tma_load_3d(sbase + OFF_RING + s * SLOT_BYTES, &tm_wl3, 0, (job / 3) * 32, 2 * s, sbase + OFF_JB2);
                        }
                        for (int kc = 0; kc < 6; kc++) mbar_wait(sbase + OFF_FULL + (3 + kc) * 8, 0);
                        mbar_wait(sbase + OFF_JB2, jph);
                    }
                    float ja[16];
#define JOBK(k) wgmma_ss32<((k) > 0), (k) * 128, ((k) >> 2) * 256 + ((k) & 3) * 2>(ja, cx.da0);
                    mbar_wait(sbase + OFF_FULL, 0);
                    wg_fence();
                    JOBK(0)  JOBK(1)  JOBK(2)  JOBK(3)  JOBK(4)  JOBK(5)  JOBK(6)  JOBK(7)
                    wg_commit();
                    mbar_wait(sbase + OFF_FULL + 8, 0);
                    wg_fence();
                    JOBK(8)  JOBK(9)  JOBK(10) JOBK(11) JOBK(12) JOBK(13) JOBK(14) JOBK(15)
                    wg_commit();
                    mbar_wait(sbase + OFF_FULL + 16, 0);
                    wg_fence();
                    JOBK(16) JOBK(17) JOBK(18) JOBK(19) JOBK(20) JOBK(21) JOBK(22) JOBK(23)
#undef JOBK
                    wg_commit();
                    wg_wait<0>();
                    const int fidx = (cb * NFRAG + (job / 3) * 2) * 128 + wtid;
                    uint4* dst = scr->wfrag + (par & 1) * (6 * NFRAG * 128) + fidx;
#pragma unroll
                    for (int i = 0; i < 2; i++) {
                        asm volatile("st.relaxed.gpu.global.v4.u32 [%0], {%1, %2, %3, %4};" ::"l"(dst + i * 128),
                                     "r"(pack_neg(ja[8 * i + 0], ja[8 * i + 1])), "r"(pack_neg(ja[8 * i + 2], ja[8 * i + 3])),
                                     "r"(pack_neg(ja[8 * i + 4], ja[8 * i + 5])), "r"(pack_neg(ja[8 * i + 6], ja[8 * i + 7])) : "memory");
                    }
                }
                if (job + npair < NJOBS) asm volatile("bar.sync 4, 384;" ::: "memory");
                if (job != pair) jph ^= 1;
            }
        }

        par &= 1;
        mbar_wait(sbase + OFF_FULL, 0);
        mbar_wait(sbase + OFF_FULL + 8, 0);
        mbar_wait(sbase + OFF_FULL + 16, 0);
        asm volatile("bar.sync 6, 384;" ::: "memory");
        if (cx.signal) {
            mbar_arrive_cluster(cx.empty_tgt);
            mbar_arrive_cluster(cx.empty_tgt + 8);
            mbar_arrive_cluster(cx.empty_tgt + 16);
        }
        auto pack_q = [&]() {
            uint32_t all = 0;
#pragma unroll
            for (int i = 0; i < 16; i++) {
                qp[i] = pack_bf16(acc[2 * i], acc[2 * i + 1]);
                if (i >= 4) all |= qp[i];
            }
            qp[3] |= all & zero;
        };
        bool ready = false;
        uint32_t pu = 0;
#define CHUNK(N, MODE) chunk<N, MODE, false>(acc, W, qp, zero, cx, pu, ready, wg)

        const uint4* wsrc = scr->wfrag + (par * 6 + cb) * (NFRAG * 128) + wtid;
        auto load_w = [&](int kc) {
#pragma unroll
            for (int s = 4 * kc; s < 4 * kc + 4; s++) {
                asm volatile("ld.relaxed.gpu.global.v4.u32 {%0, %1, %2, %3}, [%4];"
                             : "=r"(W[4 * s]), "=r"(W[4 * s + 1]), "=r"(W[4 * s + 2]), "=r"(W[4 * s + 3])
                             : "l"(wsrc + s * 128) : "memory");
            }
        };
        auto check_w = [&](int kc) {
            uint32_t* w = kc < 6 ? W + 16 * kc : qp;
            asm volatile(
                "{\n.reg .pred p, q;\n.reg .u32 m, n;\n"
                "mov.u32 n, %17;\n"
                "CHK_%=:\n"
                "setp.ne.u32 q, n, 0;\n"
                "@q ld.relaxed.gpu.global.v4.u32 {%0, %1, %2, %3}, [%16];\n"
                "@q ld.relaxed.gpu.global.v4.u32 {%4, %5, %6, %7}, [%16 + 2048];\n"
                "@q ld.relaxed.gpu.global.v4.u32 {%8, %9, %10, %11}, [%16 + 4096];\n"
                "@q ld.relaxed.gpu.global.v4.u32 {%12, %13, %14, %15}, [%16 + 6144];\n"
                "min.u32 m, %0, %1;\n min.u32 m, m, %2;\n min.u32 m, m, %3;\n min.u32 m, m, %4;\n min.u32 m, m, %5;\n"
                "min.u32 m, m, %6;\n min.u32 m, m, %7;\n min.u32 m, m, %8;\n min.u32 m, m, %9;\n min.u32 m, m, %10;\n"
                "min.u32 m, m, %11;\n min.u32 m, m, %12;\n min.u32 m, m, %13;\n min.u32 m, m, %14;\n min.u32 m, m, %15;\n"
                "add.u32 n, n, 1;\n"
                "setp.eq.u32 p, m, 0;\n"
                "setp.lt.and.u32 p, n, 5000000, p;\n"
                "vote.sync.any.pred p, p, 0xffffffff;\n"
                "@p bra.uni CHK_%=;\n}"
                : "+r"(w[0]), "+r"(w[1]), "+r"(w[2]), "+r"(w[3]), "+r"(w[4]), "+r"(w[5]), "+r"(w[6]), "+r"(w[7]),
                  "+r"(w[8]), "+r"(w[9]), "+r"(w[10]), "+r"(w[11]), "+r"(w[12]), "+r"(w[13]), "+r"(w[14]), "+r"(w[15])
                : "l"(wsrc + kc * 512), "r"(zero) : "memory");
        };
        const uint32_t stage = sbase + OFF_WOUT + wg * WOUT_SLICE + 2 * 8192;
        const uint32_t st_addr = stage + (((lane >> 4) * 8 + (lane & 7)) << 7)
                               + (((((warp & 3) << 1) | ((lane >> 3) & 1)) ^ (lane & 7)) << 4);
        auto publish = [&](int s) {
            if (pair == (NJOBS + s) % npair) {
                uint32_t a[4];
                asm volatile("ldmatrix.sync.aligned.m8n8.x4.trans.shared.b16 {%0, %1, %2, %3}, [%4];"
                             : "=r"(a[0]), "=r"(a[1]), "=r"(a[2]), "=r"(a[3]) : "r"(st_addr + s * 8192) : "memory");
                asm volatile("st.relaxed.gpu.global.v4.u32 [%0], {%1, %2, %3, %4};" ::"l"(wsrc + (24 + s) * 128),
                             "r"(enc_neg(a[0])), "r"(enc_neg(a[1])), "r"(enc_neg(a[2])), "r"(enc_neg(a[3])) : "memory");
            }
        };
        CHUNK(0, COARSE);
        CHUNK(1, COARSE);
        CHUNK(2, COARSE);
        publish(0);
        load_w(0);
        CHUNK(3, COARSE);
        publish(1);
        load_w(1);
        CHUNK(4, COARSE);
        publish(2);
        load_w(2);
        CHUNK(5, COARSE);
        publish(3);
        wg_wait<0>();
        release<5>(cx);
        pack_q();

        auto flush_part = [&](int row, int part, bool on = true) {
            if (part == 0) {
                asm volatile("fence.proxy.async.shared::cta;" ::: "memory");
                named_bar(wg);
            }
            if (wtid == 0 && on) {
                tma_store_2d(&tm_out, cb * 64, row + (part >> 1) * HW + (part & 1) * 16, stage + part * 8192, POLICY_EVICT_FIRST);
                if (part == 3) asm volatile("cp.async.bulk.commit_group;" ::: "memory");
            }
        };
        auto init_acc = [&](int t) {
#pragma unroll
            for (int b = 0; b < 2; b++) {
#pragma unroll
                for (int h = 0; h < 2; h++) {
                    const uint32_t q = qp[t * 4 + b * 2 + h];
                    const float lo = __uint_as_float(q << 16), hi = __uint_as_float(q & 0xffff0000u);
#pragma unroll
                    for (int dy = 0; dy < 2; dy++) {
                        acc[16 * dy + 8 * b + 2 * h]         = dy ? dup(lo, one) : lo;
                        acc[16 * dy + 8 * b + 2 * h + 1]     = dup(lo, one);
                        acc[16 * dy + 8 * b + 4 + 2 * h]     = dy ? dup(hi, one) : hi;
                        acc[16 * dy + 8 * b + 4 + 2 * h + 1] = dup(hi, one);
                    }
                }
            }
        };
        auto stage_tile = [&](int slot) {
            if (wtid == 0) asm volatile("cp.async.bulk.wait_group.read 0;" ::: "memory");
            named_bar(wg);
            wg_wait<0>();
            if (cx.signal) mbar_arrive_cluster(cx.empty_tgt + slot * 8);
#pragma unroll
            for (int i = 0; i < 8; i += 2) {
                stsm_x4_t(st_addr + i * 4096,
                          pack_bf16(acc[4 * i + 0], acc[4 * i + 1]), pack_bf16(acc[4 * i + 2], acc[4 * i + 3]),
                          pack_bf16(acc[4 * i + 4], acc[4 * i + 5]), pack_bf16(acc[4 * i + 6], acc[4 * i + 7]));
            }
        };

        auto load_wo = [&]() {
#pragma unroll
            for (int s = 0; s < 4; s++) {
                asm volatile("ld.global.ca.v4.u32 {%0, %1, %2, %3}, [%4];"
                             : "=r"(qp[4 * s]), "=r"(qp[4 * s + 1]), "=r"(qp[4 * s + 2]), "=r"(qp[4 * s + 3])
                             : "l"(wsrc + (24 + s) * 128) : "memory");
            }
        };

        init_acc(0);
        check_w(0);
        load_w(3);
        load_w(4);
        CHUNK(6, FINE);
        check_w(1);
        CHUNK(7, FINE);
        check_w(2);
        CHUNK(8, FINE);
        check_w(3);
        load_w(5);
        CHUNK(9, FINE);
        check_w(4);
        CHUNK(10, FINE);
        check_w(5);
        CHUNK(11, FINE);

        int seg = pair;
        int prow = seg_row(seg);
        while (true) {
            stage_tile(slot_of<11>());
            init_acc(1);
            CHUNK(12, FINE);
            flush_part(prow, 0);
            CHUNK(13, FINE);
            CHUNK(14, FINE);
            flush_part(prow, 1);
            CHUNK(15, FINE);
            flush_part(prow, 2);
            CHUNK(16, FINE);
            flush_part(prow, 3);
            CHUNK(17, FINE);
            seg += npair;
            prow = seg_row(seg);
            stage_tile(slot_of<17>());
            init_acc(2);
            CHUNK(18, FINE);
            flush_part(prow, 0);
            CHUNK(19, FINE);
            CHUNK(20, FINE);
            flush_part(prow, 1);
            CHUNK(21, FINE);
            flush_part(prow, 2);
            CHUNK(22, FINE);
            flush_part(prow, 3);
            CHUNK(23, FINE);
            seg += npair;
            prow = seg_row(seg);
            stage_tile(slot_of<23>());
            init_acc(3);
            CHUNK(24, FINE);
            flush_part(prow, 0);
            CHUNK(25, FINE);
            load_wo();
            CHUNK(26, FINE);
            flush_part(prow, 1);
            CHUNK(27, FINE);
            flush_part(prow, 2);
            CHUNK(28, FINE);
            flush_part(prow, 3);
            CHUNK(29, FINE);
            seg += npair;
            prow = seg_row(seg);
            const bool tail = seg + 5 * npair >= NSEG;
            stage_tile(slot_of<29>());
            CHUNK(30, COARSE);
            flush_part(prow, 0, !tail);
            CHUNK(31, COARSE);
            check_w(6);
            CHUNK(32, COARSE_REG);
            CHUNK(33, COARSE_REG);
            flush_part(prow, 1, !tail);
            CHUNK(34, COARSE_REG);
            CHUNK(35, COARSE_REG);
            if (tail) break;
            wg_wait<0>();
            release<35>(cx);
            pack_q();
            init_acc(0);
            CHUNK(36, FINE);
            flush_part(prow, 2);
            CHUNK(37, FINE);
            CHUNK(38, FINE);
            CHUNK(39, FINE);
            flush_part(prow, 3);
            CHUNK(40, FINE);
            CHUNK(41, FINE);
            seg += npair;
            prow = seg_row(seg);
            pu ^= 1;
        }
#undef CHUNK

        wg_wait<0>();
        release<35>(cx);
        pack_q();
        auto send = [&](auto mc) {
            constexpr int m = decltype(mc)::v, off = piece_off(m);
            if (m % 4 == 0 && m > 0) prow = seg_row(seg + (m / 4) * npair);
            if (wtid == 0)
                tma_store_2d(&tm_out, cb * 64, prow + (m / 2 % 2) * HW + (m % 2) * 16, stage - 16384 + off, POLICY_EVICT_FIRST);
        };
        auto after = [&](auto tc, auto pc) {
            constexpr int t = decltype(tc)::v, pos = decltype(pc)::v, m = sched_sent(t, pos), n = sched_sent(t, pos + 1) - m;
            if (pos == 0 && t > 1) {
                asm volatile("fence.proxy.async.shared::cta;" ::: "memory");
                named_bar(wg);
            }
            if (n > 0) send(IC<m>{});
        };
        auto stage_piece = [&](auto mc) {
            constexpr int off = piece_off(decltype(mc)::v), i = decltype(mc)::v % 4 * 8;
            stsm_x4_t(st_addr - 16384 + off, pack_bf16(acc[i + 0], acc[i + 1]), pack_bf16(acc[i + 2], acc[i + 3]),
                                             pack_bf16(acc[i + 4], acc[i + 5]), pack_bf16(acc[i + 6], acc[i + 7]));
        };
#define TCHUNK(T, K) chunk<30 + 6 * T + K, FINE, true>(acc, W, qp, zero, cx, pu, ready, wg); after(IC<T>{}, IC<K>{});
#define TAIL_TILE(T)                                                                                          \
        init_acc(T - 1);                                                                                      \
        TCHUNK(T, 0) TCHUNK(T, 1) TCHUNK(T, 2) TCHUNK(T, 3) TCHUNK(T, 4) TCHUNK(T, 5)                         \
        wg_wait<0>();                                                                                         \
        release<35 + 6 * T>(cx);                                                                              \
        stage_piece(IC<4 * T>{}); stage_piece(IC<4 * T + 1>{}); stage_piece(IC<4 * T + 2>{}); stage_piece(IC<4 * T + 3>{});
        TAIL_TILE(1) TAIL_TILE(2) TAIL_TILE(3) TAIL_TILE(4)
#undef TAIL_TILE
#undef TCHUNK
        after(IC<5>{}, IC<0>{});
        send(IC<16>{}); send(IC<17>{}); send(IC<18>{}); send(IC<19>{});
        if (wtid == 0) asm volatile("cp.async.bulk.commit_group;" ::: "memory");
        if (wtid == 0) asm volatile("cp.async.bulk.wait_group.read 0;" ::: "memory");
    } else {
        asm volatile("setmaxnreg.dec.sync.aligned.u32 32;");
        if (warp == 12) {
            asm volatile("bar.sync 5, 448;" ::: "memory");
            if (elect_one()) {
                const int g1 = (pair + 1) % 3, g2 = (pair + 2) % 3;
#pragma unroll 1
                for (int kc = 0; kc < 6; kc++) {
                    const uint32_t bar = sbase + OFF_FULL + (3 + kc) * 8;
                    mbar_expect_tx(bar, (kc & 1) ? SLOT_BYTES : 5 * SLOT_BYTES);
                    tma_load_5d(sbase + OFF_RING + (3 + kc) * SLOT_BYTES, &tm_p8, kc * 64, pair * 2, 0, bar);
                    if (!(kc & 1)) {
                        tma_load_2d(sbase + OFF_WOUT + g1 * WOUT_SLICE + kc * 8192, &tm_wo, rank * 192 + g1 * 64, kc * 64, bar);
                        tma_load_2d(sbase + OFF_WOUT + g2 * WOUT_SLICE + kc * 8192, &tm_wo, rank * 192 + g2 * 64, kc * 64, bar);
                    }
                }
            }
            __syncwarp();
        }
        asm volatile("barrier.cluster.wait.aligned;" ::: "memory");
        if (warp == 12) {
            if ((sbase & 0x3FFFFu) != SMEM_BASE) asm volatile("trap;");
            const uint32_t dst0 = sbase + OFF_RING + rank * 4096;
            uint32_t so = 9 * 8, ph = 1, step = 6;
            auto next_slot = [&]() {
                so += 8;
                if (so == NSLOTS * 8) { so = 0; ph ^= 1; }
            };
            unsigned mytiles = 0, seen = 0;
            auto look = [&]() {
                asm volatile("ld.relaxed.gpu.global.u32 %0, [%1];" : "=r"(seen) : "l"(&scr->prog) : "memory");
            };
            auto tile = [&](bool coarse, int coord, uint64_t pol, bool last) {
                if (rank == 0 && mytiles >= GOV_START) {
                    const unsigned need = mytiles * npair - 2 * max(GOV_TIGHT - (int)mytiles, 0);
                    unsigned spins = 0;
                    while (__any_sync(0xffffffffu, (int)(need - seen) > 0) && ++spins < 100000u) look();
                }
                mytiles++;
#pragma unroll
                for (int kc = 0; kc < 6; kc++) {
                    const uint32_t bar = sbase + OFF_FULL + so, dst = dst0 + so * (SLOT_BYTES / 8);
                    mbar_wait_bounded(sbase + OFF_EMPTY + so, ph);
                    step++;
                    if (elect_one()) {
                        mbar_expect_tx(bar, SLOT_BYTES);
                        if (coarse) tma_load_5d_mc(dst, &tm_p, kc * 64, pair * 2, coord, bar, pol);
                        else        tma_load_2d_mc(dst, &tm_c, kc * 64, coord, bar, pol);
                        asm volatile("st.volatile.shared.u32 [%0], %1;" ::"r"(sbase + OFF_PACE), "r"(step) : "memory");
                    }
                    if (kc == 0 && rank == 0 && lane == 0 && !last)
                        asm volatile("red.relaxed.gpu.global.add.u32 [%0], 1;" ::"l"(&scr->prog) : "memory");
                    next_slot();
                    if (kc == 3 && rank == 0) look();
                }
            };
            const int ntiles = nfine + nfine / 4;
#pragma unroll 1
            for (int i = 1; i < ntiles; i++) {
                int j;
                const bool coarse = tile_of(i, j);
                tile(coarse, coarse ? j + 2 * rank : seg_row(j * npair + pair) + rank * HW,
                     i >= ntiles - EF_TILES ? POLICY_EVICT_FIRST : POLICY_EVICT_NORMAL, i + 1 == ntiles);
            }
            if (rank == 0 && lane == 0) {
                if (atomicAdd(&scr->prog, 1u) + 1 == mytiles * npair) {
                    asm volatile("st.relaxed.gpu.global.u32 [%0], 0;" ::"l"(&scr->prog) : "memory");
                    asm volatile("red.relaxed.gpu.global.add.u32 [%0], 1;" ::"l"(&scr->epoch) : "memory");
                }
            }
            __syncwarp();
#pragma unroll 1
            for (int s = 0; s < NSLOTS; s++) {
                mbar_wait_bounded(sbase + OFF_EMPTY + so, ph);
                next_slot();
            }
        } else if (warp == 13) {
            auto wait_pace = [&](int need) {
                unsigned spins = 0;
                while (true) {
                    uint32_t v;
                    asm volatile("ld.volatile.shared.u32 %0, [%1];" : "=r"(v) : "r"(sbase + OFF_PACE) : "memory");
                    if ((int)v >= need || ++spins > 4000000u) break;
                    __nanosleep(20);
                }
            };
            if (lane == 0) mbar_expect_tx(sbase + OFF_NB, 12 * 512);
#pragma unroll 1
            for (int k = 0; k < 12; k++) {
                const int j = k < 6 ? 2 : 3;
                wait_pace(PF_FIRST + k * 3 / 4);
                if (lane == 0)
                    tma_load_2d(sbase + OFF_SINK, &tm_cf, 0, (seg_row(j * npair + pair) + rank * HW) * 6 + (k - (j - 2) * 6) * 32,
                                sbase + OFF_NB);
            }
#pragma unroll 1
            for (int i = 5; i < nfine + nfine / 4; i++) {
                int j;
                const char *b0, *b1;
                if (tile_of(i, j)) {
                    b0 = (const char*)p_ptr + (size_t)((j + 2 * rank) * npair + pair) * (16 * C * 2);
                    b1 = b0 + (size_t)npair * (16 * C * 2);
                } else {
                    b0 = (const char*)c_ptr + (size_t)(seg_row(j * npair + pair) + rank * HW) * (C * 2);
                    b1 = b0 + 16 * C * 2;
                }
                wait_pace(6 * i - max(PF_LEAD0 - max(i - PF_DECAY, 0), PF_LEAD));
#pragma unroll
                for (int k = 0; k < 6; k++) {
                    asm volatile("prefetch.global.L2 [%0];" ::"l"((k < 3 ? b0 : b1) + lane * 128 + (k % 3) * 4096) : "memory");
                    __nanosleep(PF_GAP);
                }
            }
            mbar_wait_bounded(sbase + OFF_NB, 0);
        } else if (warp == 15) {
            uint32_t par;
            asm volatile("ld.relaxed.gpu.global.u32 %0, [%1];" : "=r"(par) : "l"(&scr->epoch) : "memory");
            uint4* clr = scr->wfrag + (~par & 1) * (6 * NFRAG * 128);
#pragma unroll 1
            for (int i = blockIdx.x * 32 + lane; i < 6 * NFRAG * 128; i += npair * 64) clr[i] = make_uint4(0u, 0u, 0u, 0u);
        }
    }
}

typedef CUresult (*EncodeFn)(CUtensorMap*, CUtensorMapDataType, cuuint32_t, void*, const cuuint64_t*, const cuuint64_t*,
                             const cuuint32_t*, const cuuint32_t*, CUtensorMapInterleave, CUtensorMapSwizzle,
                             CUtensorMapL2promotion, CUtensorMapFloatOOBfill);

void encode(EncodeFn fn, CUtensorMap* tm, const void* ptr, int rank, const cuuint64_t* dims, const cuuint64_t* strides,
            const cuuint32_t* box, CUtensorMapSwizzle swizzle = CU_TENSOR_MAP_SWIZZLE_128B,
            CUtensorMapL2promotion promotion = CU_TENSOR_MAP_L2_PROMOTION_NONE) {
    const cuuint32_t es[5] = {1, 1, 1, 1, 1};
    fn(tm, CU_TENSOR_MAP_DATA_TYPE_BFLOAT16, (cuuint32_t)rank, const_cast<void*>(ptr), dims, strides, box, es,
       CU_TENSOR_MAP_INTERLEAVE_NONE, swizzle, promotion, CU_TENSOR_MAP_FLOAT_OOB_FILL_NONE);
}

}

extern "C" void kernel_launch(void* const* d_in, const int* in_sizes, int n_in, void* d_out, int out_size) {
    (void)in_sizes; (void)n_in; (void)out_size;
    const __nv_bfloat16* c_fine   = (const __nv_bfloat16*)d_in[0];
    const __nv_bfloat16* p_coarse = (const __nv_bfloat16*)d_in[1];
    const __nv_bfloat16* w_lat    = (const __nv_bfloat16*)d_in[2];
    const __nv_bfloat16* w_out    = (const __nv_bfloat16*)d_in[3];

    static EncodeFn fn = nullptr;
    static int np = 0;
    static Scratch* scr = nullptr;
    if (!fn) {
        void* p = nullptr;
        cudaDriverEntryPointQueryResult qr;
        cudaGetDriverEntryPoint("cuTensorMapEncodeTiled", &p, cudaEnableDefault, &qr);
        fn = (EncodeFn)p;
        cudaGetSymbolAddress((void**)&scr, g_scratch);
        cudaFuncSetAttribute(fpn_kernel<NPAIRS>, cudaFuncAttributeMaxDynamicSharedMemorySize, SMEM_BYTES);
        cudaFuncSetAttribute(fpn_kernel<0>, cudaFuncAttributeMaxDynamicSharedMemorySize, SMEM_BYTES);
        cudaLaunchConfig_t cfg = {};
        cfg.gridDim = dim3(2); cfg.blockDim = dim3(NTHREADS); cfg.dynamicSmemBytes = SMEM_BYTES;
        cudaLaunchAttribute at[1];
        at[0].id = cudaLaunchAttributeClusterDimension;
        at[0].val.clusterDim.x = 2; at[0].val.clusterDim.y = 1; at[0].val.clusterDim.z = 1;
        cfg.attrs = at; cfg.numAttrs = 1;
        if (cudaOccupancyMaxActiveClusters(&np, fpn_kernel<0>, &cfg) != cudaSuccess || np < 1) np = 1;
        if (np > NPAIRS) np = NPAIRS;
        while ((NSEG / 4) % np) np--;
    }

    CUtensorMap tm_cf, tm_c, tm_p, tm_wl3, tm_out, tm_p8, tm_wo;
    {
        const cuuint64_t dims[2] = {(cuuint64_t)C, (cuuint64_t)NPIX};
        const cuuint64_t str[1]  = {(cuuint64_t)C * 2};
        const cuuint32_t box_in[2]  = {64, 32};
        const cuuint32_t box_out[2] = {64, 16};
        encode(fn, &tm_c, c_fine, 2, dims, str, box_in);
        encode(fn, &tm_out, d_out, 2, dims, str, box_out);
    }
    {
        const cuuint64_t dims[5] = {(cuuint64_t)C, 2, 4, (cuuint64_t)(2 * np), (cuuint64_t)(NSEG / np)};
        const cuuint64_t str[4]  = {(cuuint64_t)4 * C * 2, (cuuint64_t)C * 2, (cuuint64_t)8 * C * 2, (cuuint64_t)np * 16 * C * 2};
        const cuuint32_t box[5]  = {64, 2, 4, 2, 2};
        encode(fn, &tm_p, p_coarse, 5, dims, str, box);
        const cuuint32_t box8[5] = {64, 2, 4, 2, 4};
        encode(fn, &tm_p8, p_coarse, 5, dims, str, box8);
    }
    {
        const cuuint64_t dims[2] = {(cuuint64_t)C, (cuuint64_t)C};
        const cuuint64_t str[1]  = {(cuuint64_t)C * 2};
        const cuuint32_t box[2] = {64, 128};
        encode(fn, &tm_wo, w_out, 2, dims, str, box);
    }
    {
        const cuuint64_t dims[3] = {64, (cuuint64_t)C, 6};
        const cuuint64_t str[2]  = {(cuuint64_t)C * 2, 128};
        const cuuint32_t box[3]  = {64, 32, 2};
        encode(fn, &tm_wl3, w_lat, 3, dims, str, box);
    }
    {
        const cuuint64_t dims[2] = {64, (cuuint64_t)NPIX * 6};
        const cuuint64_t str[1]  = {128};
        const cuuint32_t box[2]  = {8, 32};
        encode(fn, &tm_cf, c_fine, 2, dims, str, box, CU_TENSOR_MAP_SWIZZLE_NONE, CU_TENSOR_MAP_L2_PROMOTION_L2_128B);
    }
    auto kernel = np == NPAIRS ? fpn_kernel<NPAIRS> : fpn_kernel<0>;
    kernel<<<2 * np, NTHREADS, SMEM_BYTES>>>(scr, c_fine, p_coarse, NSEG / np, 1.0f, 0u,
                                             tm_wo, tm_wl3, tm_p8, tm_c, tm_p, tm_out, tm_cf);
}
```

```cpp
#include <cuda_runtime.h>
#include <cuda_bf16.h>
#include <cuda.h>
#include <stdint.h>

namespace {

constexpr int C          = 384;
constexpr int HW         = 384;
constexpr int NPIX       = HW * HW;
constexpr int NSEG       = NPIX / 64;
constexpr int NJOBS      = 36;

constexpr int NFRAG      = 28;
constexpr int NSLOTS     = 10;
constexpr int NPAIRS     = 64;
constexpr int PF_LEAD    = 5;
constexpr int PF_LEAD0   = 18;
constexpr int PF_DECAY   = 12;
constexpr int PF_FIRST   = 11;
constexpr int PF_GAP     = 50;
constexpr int GOV_START  = 12;
constexpr int GOV_TIGHT  = 26;
constexpr int EF_TILES   = 13;
constexpr int SCHED      = 2266;

constexpr int SLOT_BYTES  = 8192;
constexpr int WOUT_SLICE  = 384 * 128;
constexpr int OFF_WOUT    = 0;
constexpr int OFF_RING    = 3 * WOUT_SLICE;
constexpr int OFF_FULL    = OFF_RING + NSLOTS * SLOT_BYTES;
constexpr int OFF_EMPTY   = OFF_FULL + 8 * NSLOTS;
constexpr int OFF_JB2     = OFF_EMPTY + 8 * NSLOTS;
constexpr int OFF_PACE    = OFF_JB2 + 8;
constexpr int OFF_NB      = OFF_PACE + 8;
constexpr int OFF_SINK    = (OFF_NB + 8 + 127) / 128 * 128;
constexpr int SMEM_BYTES  = OFF_SINK + 512;
static_assert(SMEM_BYTES <= 232448, "smem");
static_assert(NSLOTS == 10, "a unit (30 ring items) must be an odd number of rounds of the ring");

constexpr int      SMEM_BASE = 1024;
constexpr uint64_t DESC_RING = 0x4000004000010000ull + ((SMEM_BASE + OFF_RING) >> 4);

constexpr int NTHREADS = 512;
constexpr uint64_t POLICY_EVICT_FIRST  = 0x12F0000000000000ull;
constexpr uint64_t POLICY_EVICT_NORMAL = 0x1000000000000000ull;

struct Scratch {
    uint4    wfrag[2 * 6 * NFRAG * 128];
    unsigned epoch;
    unsigned pad0[31];
    unsigned prog;
};
__device__ Scratch g_scratch;

__device__ __forceinline__ uint32_t smem_u32(const void* p) { return (uint32_t)__cvta_generic_to_shared(p); }

__device__ __forceinline__ void mbar_init(uint32_t bar, uint32_t cnt) {
    asm volatile("mbarrier.init.shared::cta.b64 [%0], %1;" ::"r"(bar), "r"(cnt) : "memory");
}
__device__ __forceinline__ void mbar_expect_tx(uint32_t bar, uint32_t bytes) {
    asm volatile("mbarrier.arrive.expect_tx.shared::cta.b64 _, [%0], %1;" ::"r"(bar), "r"(bytes) : "memory");
}
__device__ __forceinline__ void mbar_wait_bounded(uint32_t bar, uint32_t parity) {
    asm volatile(
        "{\n"
        ".reg .pred p;\n"
        ".reg .u32 n;\n"
        "mbarrier.try_wait.parity.shared::cta.b64 p, [%0], %1;\n"
        "@p bra DONE_%=;\n"
        "mov.u32 n, 0;\n"
        "WAIT_%=:\n"
        "mbarrier.try_wait.parity.shared::cta.b64 p, [%0], %1;\n"
        "@p bra DONE_%=;\n"
        "add.u32 n, n, 1;\n"
        "setp.lt.u32 p, n, 4000000;\n"
        "@p bra WAIT_%=;\n"
        "trap;\n"
        "DONE_%=:\n"
        "}\n" ::"r"(bar), "r"(parity) : "memory");
}
__device__ __forceinline__ void mbar_wait(uint32_t bar, uint32_t parity) {
    asm volatile(
        "{\n"
        ".reg .pred p;\n"
        "WAIT_%=:\n"
        "mbarrier.try_wait.parity.shared::cta.b64 p, [%0], %1;\n"
        "@!p bra WAIT_%=;\n"
        "}\n" ::"r"(bar), "r"(parity) : "memory");
}
__device__ __forceinline__ bool mbar_try(uint32_t bar, uint32_t parity) {
    uint32_t r;
    asm volatile("{\n.reg .pred p;\nmbarrier.test_wait.parity.shared::cta.b64 p, [%1], %2;\nselp.u32 %0, 1, 0, p;\n}\n"
                 : "=r"(r) : "r"(bar), "r"(parity) : "memory");
    return r != 0;
}
__device__ __forceinline__ void mbar_arrive_cluster(uint32_t cluster_addr) {
    asm volatile("mbarrier.arrive.shared::cluster.b64 _, [%0];" ::"r"(cluster_addr) : "memory");
}
__device__ __forceinline__ uint32_t mapa(uint32_t addr, uint32_t rank) {
    uint32_t r;
    asm("mapa.shared::cluster.u32 %0, %1, %2;" : "=r"(r) : "r"(addr), "r"(rank));
    return r;
}
__device__ __forceinline__ void named_bar(int wg) {
    asm volatile("bar.sync %0, 128;" ::"r"(wg + 1) : "memory");
}

__device__ __forceinline__ void tma_load_2d(uint32_t dst, const CUtensorMap* tm, int c0, int c1, uint32_t bar) {
    asm volatile("cp.async.bulk.tensor.2d.shared::cluster.global.mbarrier::complete_tx::bytes [%0], [%1, {%2, %3}], [%4];"
                 ::"r"(dst), "l"(tm), "r"(c0), "r"(c1), "r"(bar) : "memory");
}
__device__ __forceinline__ void tma_load_3d(uint32_t dst, const CUtensorMap* tm, int c0, int c1, int c2, uint32_t bar) {
    asm volatile("cp.async.bulk.tensor.3d.shared::cluster.global.mbarrier::complete_tx::bytes [%0], [%1, {%2, %3, %4}], [%5];"
                 ::"r"(dst), "l"(tm), "r"(c0), "r"(c1), "r"(c2), "r"(bar) : "memory");
}
__device__ __forceinline__ void tma_load_5d(uint32_t dst, const CUtensorMap* tm, int c0, int c3, int c4, uint32_t bar) {
    asm volatile("cp.async.bulk.tensor.5d.shared::cluster.global.mbarrier::complete_tx::bytes [%0], [%1, {%2, 0, 0, %3, %4}], [%5];"
                 ::"r"(dst), "l"(tm), "r"(c0), "r"(c3), "r"(c4), "r"(bar) : "memory");
}
__device__ __forceinline__ void tma_load_2d_mc(uint32_t dst, const CUtensorMap* tm, int c0, int c1, uint32_t bar, uint64_t pol) {
    asm volatile("cp.async.bulk.tensor.2d.shared::cluster.global.mbarrier::complete_tx::bytes.multicast::cluster.L2::cache_hint"
                 " [%0], [%1, {%2, %3}], [%4], %5, %6;"
                 ::"r"(dst), "l"(tm), "r"(c0), "r"(c1), "r"(bar), "h"((uint16_t)3), "l"(pol) : "memory");
}
__device__ __forceinline__ void tma_load_5d_mc(uint32_t dst, const CUtensorMap* tm, int c0, int c3, int c4, uint32_t bar, uint64_t pol) {
    asm volatile("cp.async.bulk.tensor.5d.shared::cluster.global.mbarrier::complete_tx::bytes.multicast::cluster.L2::cache_hint"
                 " [%0], [%1, {%2, 0, 0, %3, %4}], [%5], %6, %7;"
                 ::"r"(dst), "l"(tm), "r"(c0), "r"(c3), "r"(c4), "r"(bar), "h"((uint16_t)3), "l"(pol) : "memory");
}
__device__ __forceinline__ void tma_store_2d(const CUtensorMap* tm, int c0, int c1, uint32_t src, uint64_t pol) {
    asm volatile("cp.async.bulk.tensor.2d.global.shared::cta.bulk_group.L2::cache_hint [%0, {%1, %2}], [%3], %4;"
                 ::"l"(tm), "r"(c0), "r"(c1), "r"(src), "l"(pol) : "memory");
}
__device__ __forceinline__ bool elect_one() {
    uint32_t r;
    asm volatile("{\n.reg .pred p;\nelect.sync _|p, 0xffffffff;\nselp.u32 %0, 1, 0, p;\n}" : "=r"(r));
    return r != 0;
}
__device__ __forceinline__ void prefetch_tmap(const CUtensorMap* tm) {
    asm volatile("prefetch.tensormap [%0];" ::"l"(tm) : "memory");
}

__device__ __forceinline__ void wg_fence()  { asm volatile("wgmma.fence.sync.aligned;" ::: "memory"); }
__device__ __forceinline__ void wg_commit() { asm volatile("wgmma.commit_group.sync.aligned;" ::: "memory"); }
template <int N> __device__ __forceinline__ void wg_wait() { asm volatile("wgmma.wait_group.sync.aligned %0;" ::"n"(N) : "memory"); }

#define ACC16(a)                                                                                              \
    "+f"(a[0]), "+f"(a[1]), "+f"(a[2]), "+f"(a[3]), "+f"(a[4]), "+f"(a[5]), "+f"(a[6]), "+f"(a[7]),           \
    "+f"(a[8]), "+f"(a[9]), "+f"(a[10]), "+f"(a[11]), "+f"(a[12]), "+f"(a[13]), "+f"(a[14]), "+f"(a[15])
#define ACC32(a)                                                                                              \
    ACC16(a),                                                                                                 \
    "+f"(a[16]), "+f"(a[17]), "+f"(a[18]), "+f"(a[19]), "+f"(a[20]), "+f"(a[21]), "+f"(a[22]), "+f"(a[23]),   \
    "+f"(a[24]), "+f"(a[25]), "+f"(a[26]), "+f"(a[27]), "+f"(a[28]), "+f"(a[29]), "+f"(a[30]), "+f"(a[31])
#define ACC16_STR "{%0, %1, %2, %3, %4, %5, %6, %7, %8, %9, %10, %11, %12, %13, %14, %15}"
#define ACC32_STR                                                                                             \
    "{%0, %1, %2, %3, %4, %5, %6, %7, %8, %9, %10, %11, %12, %13, %14, %15, "                                 \
    "%16, %17, %18, %19, %20, %21, %22, %23, %24, %25, %26, %27, %28, %29, %30, %31}"

template <int BOFF>
__device__ __forceinline__ void wgmma_rs(float (&d)[32], uint32_t a0, uint32_t a1, uint32_t a2, uint32_t a3) {
    asm volatile("{\n.reg .b64 db;\n"
                 "mov.b64 db, %36;\n"
                 "wgmma.mma_async.sync.aligned.m64n64k16.f32.bf16.bf16 " ACC32_STR
                 ", {%32, %33, %34, %35}, db, 1, -1, 1, 0;\n}"
                 : ACC32(d) : "r"(a0), "r"(a1), "r"(a2), "r"(a3), "n"(DESC_RING + BOFF));
}
template <int ACCUM, int AOFF, int BOFF>
__device__ __forceinline__ void wgmma_ss(float (&d)[32], uint32_t da_lo) {
    asm volatile("{\n.reg .b64 da, db;\n.reg .b32 lo;\n"
                 "add.u32 lo, %32, %34;\nmov.b64 da, {lo, 0x40000040};\n"
                 "mov.b64 db, %35;\n"
                 "wgmma.mma_async.sync.aligned.m64n64k16.f32.bf16.bf16 " ACC32_STR
                 ", da, db, %33, 1, 1, 1, 0;\n}"
                 : ACC32(d) : "r"(da_lo), "n"(ACCUM), "n"(AOFF), "n"(DESC_RING + BOFF));
}
template <int ACCUM, int AOFF, int BOFF>
__device__ __forceinline__ void wgmma_ss32(float (&d)[16], uint32_t da_lo) {
    asm volatile("{\n.reg .b64 da, db;\n.reg .b32 lo;\n"
                 "add.u32 lo, %16, %18;\nmov.b64 da, {lo, 0x40000040};\n"
                 "mov.b64 db, %19;\n"
                 "wgmma.mma_async.sync.aligned.m64n32k16.f32.bf16.bf16 " ACC16_STR
                 ", da, db, %17, 1, 1, 1, 0;\n}"
                 : ACC16(d) : "r"(da_lo), "n"(ACCUM), "n"(AOFF), "n"(DESC_RING + BOFF));
}
__device__ __forceinline__ uint32_t desc_lo(uint32_t addr) { return ((addr & 0x3FFFFu) >> 4) | (1u << 16); }
__device__ __forceinline__ uint32_t pack_bf16(float lo, float hi) {
    uint32_t r;
    asm("cvt.rn.bf16x2.f32 %0, %1, %2;" : "=r"(r) : "f"(hi), "f"(lo));
    return r;
}
__device__ __forceinline__ uint32_t enc_neg(uint32_t pair) {
    const uint32_t v = pair ^ 0x80008000u;
    return v == 0u ? 0x80008000u : v;
}
__device__ __forceinline__ uint32_t pack_neg(float lo, float hi) { return enc_neg(pack_bf16(lo, hi)); }
template <int V>
__device__ __forceinline__ float dup(float x, float one) {
    float r;
    if (V == 0) asm volatile("mul.rn.f32 %0, %1, %2;" : "=f"(r) : "f"(x), "f"(one));
    if (V == 1) asm volatile("mul.rz.f32 %0, %1, %2;" : "=f"(r) : "f"(x), "f"(one));
    if (V == 2) asm volatile("mul.rp.f32 %0, %1, %2;" : "=f"(r) : "f"(x), "f"(one));
    return r;
}
__device__ __forceinline__ void stsm_x4_t(uint32_t addr, uint32_t r0, uint32_t r1, uint32_t r2, uint32_t r3) {
    asm volatile("stmatrix.sync.aligned.m8n8.x4.trans.shared.b16 [%0], {%1, %2, %3, %4};"
                 ::"r"(addr), "r"(r0), "r"(r1), "r"(r2), "r"(r3) : "memory");
}

struct Ctx {
    uint32_t sbase;
    uint32_t da0;
    uint32_t empty_tgt;
    bool     signal;
};

template <int N> __device__ __forceinline__ constexpr uint32_t slot_of() { return (3 + N) % NSLOTS; }
template <int N> __device__ __forceinline__ uint32_t phase_of(uint32_t pu) { return pu ^ (((3 + N) / NSLOTS) & 1); }
template <int N> __device__ __forceinline__ void release(const Ctx& cx) {
    if (cx.signal) mbar_arrive_cluster(cx.empty_tgt + slot_of<N>() * 8);
}

enum { FINE, COARSE, COARSE_REG };
template <int N, int MODE, bool SKEW>
__device__ __forceinline__ void chunk(float (&acc)[32], const uint32_t (&W)[96], const uint32_t (&A)[16], uint32_t zero,
                                      const Ctx& cx, uint32_t pu, bool& ready, int wg) {
    constexpr int KC = N % 6;
    constexpr int B  = slot_of<N>() * 512;
    if (!ready) mbar_wait(cx.sbase + OFF_FULL + slot_of<N>() * 8, phase_of<N>(pu));
    ready = mbar_try(cx.sbase + OFF_FULL + slot_of<N + 1>() * 8, phase_of<N + 1>(pu));
    if (SKEW) {
        const int id = 8 + ((N / 6) & 1) * 4 + wg;
        if (KC == 2 && wg > 0) asm volatile("bar.sync %0, 256;" ::"r"(id - 1) : "memory");
        if (KC == 4 && wg < 2) asm volatile("bar.arrive %0, 256;" ::"r"(id) : "memory");
    }
    if (MODE == FINE) {
        wg_fence();
        wgmma_rs<B + 0>(acc, W[KC * 16 + 0],  W[KC * 16 + 1],  W[KC * 16 + 2],  W[KC * 16 + 3]);
        wgmma_rs<B + 2>(acc, W[KC * 16 + 4],  W[KC * 16 + 5],  W[KC * 16 + 6],  W[KC * 16 + 7]);
        wgmma_rs<B + 4>(acc, W[KC * 16 + 8],  W[KC * 16 + 9],  W[KC * 16 + 10], W[KC * 16 + 11]);
        wgmma_rs<B + 6>(acc, W[KC * 16 + 12], W[KC * 16 + 13], W[KC * 16 + 14], W[KC * 16 + 15]);
    } else {
        if (MODE == COARSE) {
            wg_fence();
            wgmma_ss<(KC > 0), KC * 4 * 128, B>(acc, cx.da0);
        } else {
            uint32_t a[4];
            asm volatile("{\n.reg .u32 z;\nmov.u32 z, %%clock;\nand.b32 z, z, %8;\n"
                         "xor.b32 %0, %4, z;\nxor.b32 %1, %5, z;\nxor.b32 %2, %6, z;\nxor.b32 %3, %7, z;\n}"
                         : "=r"(a[0]), "=r"(a[1]), "=r"(a[2]), "=r"(a[3])
                         : "r"(A[((KC + 2) & 3) * 4]), "r"(A[((KC + 2) & 3) * 4 + 1]), "r"(A[((KC + 2) & 3) * 4 + 2]),
                           "r"(A[((KC + 2) & 3) * 4 + 3]), "r"(zero));
            wg_fence();
            wgmma_rs<B>(acc, a[0], a[1], a[2], a[3]);
            wg_commit();
        }
        wgmma_ss<1, (KC * 4 + 1) * 128, B + 2>(acc, cx.da0);
        wgmma_ss<1, (KC * 4 + 2) * 128, B + 4>(acc, cx.da0);
        wgmma_ss<1, (KC * 4 + 3) * 128, B + 6>(acc, cx.da0);
    }
    wg_commit();
    if (KC > 0) {
        wg_wait<1>();
        release<N - (KC > 0)>(cx);
    }
}

__host__ __device__ constexpr int sched_n(int t) { int v = SCHED; for (int i = t; i < 4; i++) v /= 10; return v % 10; }
__host__ __device__ constexpr int sched_sent(int t, int pos) {
    int c = 0;
    for (int i = 1; i < t; i++) c += sched_n(i);
    for (int k = 0; t <= 4 && k < sched_n(t); k++) c += k * 6 / sched_n(t) < pos;
    return c;
}
__host__ __device__ constexpr bool sched_ok() {
    for (int t = 1; t <= 4; t++) if (sched_n(t) > 6 || sched_sent(t + 1, 0) > 4 * t) return false;
    return sched_sent(5, 0) == 16;
}
static_assert(sched_ok(), "a piece is sent after its tile has been staged; only the last tile is left for the end");
__host__ __device__ constexpr int piece_off(int m) {
    return (m < 4 ? 8 + 4 * m : m < 12 ? m - 4 : 9 + (m - 12) / 3 * 4 + (m - 12) % 3) * 2048;
}
template <int V> struct IC { static constexpr int v = V; };

__device__ __forceinline__ int seg_row(int g) {
    const int y = g / 12;
    return y * (2 * HW) + (g - y * 12) * 32;
}

__device__ __forceinline__ bool tile_of(int i, int& j) {
    const int u = i / 5, t = i - u * 5;
    j = 4 * u + max(t - 1, 0);
    return t == 0;
}

template <int NP>
__global__ void __cluster_dims__(2, 1, 1) __launch_bounds__(NTHREADS, 1)
fpn_kernel(Scratch* scr, const __nv_bfloat16* __restrict__ c_ptr, const __nv_bfloat16* __restrict__ p_ptr,
           const int nsteps, const float one, const uint32_t zero,
           const __grid_constant__ CUtensorMap tm_wo, const __grid_constant__ CUtensorMap tm_wl3,
           const __grid_constant__ CUtensorMap tm_p8, const __grid_constant__ CUtensorMap tm_c,
           const __grid_constant__ CUtensorMap tm_p, const __grid_constant__ CUtensorMap tm_out,
           const __grid_constant__ CUtensorMap tm_cf)
{
    extern __shared__ __align__(1024) uint8_t smem[];
    const uint32_t sbase = smem_u32(smem);
    const int tid   = threadIdx.x;
    const int warp  = __shfl_sync(0xffffffffu, tid >> 5, 0);
    const int lane  = tid & 31;
    const int rank  = blockIdx.x & 1;
    const int pair  = blockIdx.x >> 1;
    const int npair = NP ? NP : gridDim.x >> 1;
    const int nfine = NP ? NSEG / (NP ? NP : 1) : nsteps;

    if (tid == 480) {
        prefetch_tmap(&tm_wo); prefetch_tmap(&tm_wl3); prefetch_tmap(&tm_p8);
        prefetch_tmap(&tm_c); prefetch_tmap(&tm_p); prefetch_tmap(&tm_out); prefetch_tmap(&tm_cf);
    }
    if (warp == 12 && elect_one()) {
        for (int s = 0; s < 3; s++) mbar_init(sbase + OFF_FULL + s * 8, 1);
        asm volatile("fence.mbarrier_init.release.cluster;" ::: "memory");
        asm volatile("fence.proxy.async.shared::cta;" ::: "memory");
        const int g0 = pair % 3;
#pragma unroll 1
        for (int s = 0; s < 3; s++) {
            const uint32_t bar = sbase + OFF_FULL + s * 8;
            const uint32_t dst = sbase + OFF_WOUT + g0 * WOUT_SLICE + s * 16384;
            mbar_expect_tx(bar, pair < NJOBS ? 3 * SLOT_BYTES : 2 * SLOT_BYTES);
            tma_load_2d(dst, &tm_wo, rank * 192 + g0 * 64, s * 128, bar);
            if (pair < NJOBS) tma_load_3d(sbase + OFF_RING + s * SLOT_BYTES, &tm_wl3, 0, (pair / 3) * 32, 2 * s, bar);
        }
    }
    if (warp == 13) {
        if (lane == 0) {
            for (int s = 0; s < NSLOTS; s++) {
                if (s >= 3) mbar_init(sbase + OFF_FULL + s * 8, 1);
                mbar_init(sbase + OFF_EMPTY + s * 8, 6);
            }
            mbar_init(sbase + OFF_JB2, 1);
            mbar_init(sbase + OFF_NB, 1);
            asm volatile("st.volatile.shared.u32 [%0], %1;" ::"r"(sbase + OFF_PACE), "r"(6) : "memory");
            asm volatile("fence.mbarrier_init.release.cluster;" ::: "memory");
            asm volatile("fence.proxy.async.shared::cta;" ::: "memory");
        }
        __syncwarp();
        asm volatile("bar.arrive 5, 448;" ::: "memory");
    }
    __syncwarp();
    asm volatile("barrier.cluster.arrive.relaxed.aligned;" ::: "memory");

    if (warp < 12) {
        uint32_t par;
        asm volatile("ld.relaxed.gpu.global.u32 %0, [%1];" : "=r"(par) : "l"(&scr->epoch) : "memory");
        asm volatile("setmaxnreg.inc.sync.aligned.u32 160;");
        asm volatile("bar.sync 5, 448;" ::: "memory");
        asm volatile("barrier.cluster.wait.aligned;" ::: "memory");
        const int wg   = warp >> 2;
        const int wtid = tid & 127;
        Ctx cx;
        cx.sbase     = sbase;
        cx.empty_tgt = mapa(sbase + OFF_EMPTY, warp & 1);
        cx.signal    = (lane == 0) && ((warp & 3) < 2);
        cx.da0       = desc_lo(sbase + OFF_WOUT + wg * WOUT_SLICE);
        const int cb = rank * 3 + wg;

        float    acc[32];
        uint32_t qp[16];
        uint32_t W[96];

        {
            uint32_t jph = 0;
            for (int job = pair; job < NJOBS; job += npair) {
                if (job % 3 == wg) {
                    if (job != pair) {
                        named_bar(wg);
                        if (wtid == 0) {
                            mbar_expect_tx(sbase + OFF_JB2, 6 * 4096);
                            for (int s = 0; s < 3; s++)
                                tma_load_3d(sbase + OFF_RING + s * SLOT_BYTES, &tm_wl3, 0, (job / 3) * 32, 2 * s, sbase + OFF_JB2);
                        }
                        for (int kc = 0; kc < 6; kc++) mbar_wait(sbase + OFF_FULL + (3 + kc) * 8, 0);
                        mbar_wait(sbase + OFF_JB2, jph);
                    }
                    float ja[16];
#define JOBK(k) wgmma_ss32<((k) > 0), (k) * 128, ((k) >> 2) * 256 + ((k) & 3) * 2>(ja, cx.da0);
                    mbar_wait(sbase + OFF_FULL, 0);
                    wg_fence();
                    JOBK(0)  JOBK(1)  JOBK(2)  JOBK(3)  JOBK(4)  JOBK(5)  JOBK(6)  JOBK(7)
                    wg_commit();
                    mbar_wait(sbase + OFF_FULL + 8, 0);
                    wg_fence();
                    JOBK(8)  JOBK(9)  JOBK(10) JOBK(11) JOBK(12) JOBK(13) JOBK(14) JOBK(15)
                    wg_commit();
                    mbar_wait(sbase + OFF_FULL + 16, 0);
                    wg_fence();
                    JOBK(16) JOBK(17) JOBK(18) JOBK(19) JOBK(20) JOBK(21) JOBK(22) JOBK(23)
#undef JOBK
                    wg_commit();
                    wg_wait<0>();
                    const int fidx = (cb * NFRAG + (job / 3) * 2) * 128 + wtid;
                    uint4* dst = scr->wfrag + (par & 1) * (6 * NFRAG * 128) + fidx;
#pragma unroll
                    for (int i = 0; i < 2; i++) {
                        asm volatile("st.relaxed.gpu.global.v4.u32 [%0], {%1, %2, %3, %4};" ::"l"(dst + i * 128),
                                     "r"(pack_neg(ja[8 * i + 0], ja[8 * i + 1])), "r"(pack_neg(ja[8 * i + 2], ja[8 * i + 3])),
                                     "r"(pack_neg(ja[8 * i + 4], ja[8 * i + 5])), "r"(pack_neg(ja[8 * i + 6], ja[8 * i + 7])) : "memory");
                    }
                }
                if (job + npair < NJOBS) asm volatile("bar.sync 4, 384;" ::: "memory");
                if (job != pair) jph ^= 1;
            }
        }

        par &= 1;
        mbar_wait(sbase + OFF_FULL, 0);
        mbar_wait(sbase + OFF_FULL + 8, 0);
        mbar_wait(sbase + OFF_FULL + 16, 0);
        asm volatile("bar.sync 6, 384;" ::: "memory");
        if (cx.signal) {
            mbar_arrive_cluster(cx.empty_tgt);
            mbar_arrive_cluster(cx.empty_tgt + 8);
            mbar_arrive_cluster(cx.empty_tgt + 16);
        }
        auto pack_q = [&]() {
            uint32_t all = 0;
#pragma unroll
            for (int i = 0; i < 16; i++) {
                qp[i] = pack_bf16(acc[2 * i], acc[2 * i + 1]);
                if (i >= 4) all |= qp[i];
            }
            qp[3] |= all & zero;
        };
        bool ready = false;
        uint32_t pu = 0;
#define CHUNK(N, MODE) chunk<N, MODE, false>(acc, W, qp, zero, cx, pu, ready, wg)

        const uint4* wsrc = scr->wfrag + (par * 6 + cb) * (NFRAG * 128) + wtid;
        auto load_w = [&](int kc) {
#pragma unroll
            for (int s = 4 * kc; s < 4 * kc + 4; s++) {
                asm volatile("ld.relaxed.gpu.global.v4.u32 {%0, %1, %2, %3}, [%4];"
                             : "=r"(W[4 * s]), "=r"(W[4 * s + 1]), "=r"(W[4 * s + 2]), "=r"(W[4 * s + 3])
                             : "l"(wsrc + s * 128) : "memory");
            }
        };
        auto check_w = [&](int kc) {
            uint32_t* w = kc < 6 ? W + 16 * kc : qp;
            asm volatile(
                "{\n.reg .pred p, q;\n.reg .u32 m, n;\n"
                "mov.u32 n, %17;\n"
                "CHK_%=:\n"
                "setp.ne.u32 q, n, 0;\n"
                "@q ld.relaxed.gpu.global.v4.u32 {%0, %1, %2, %3}, [%16];\n"
                "@q ld.relaxed.gpu.global.v4.u32 {%4, %5, %6, %7}, [%16 + 2048];\n"
                "@q ld.relaxed.gpu.global.v4.u32 {%8, %9, %10, %11}, [%16 + 4096];\n"
                "@q ld.relaxed.gpu.global.v4.u32 {%12, %13, %14, %15}, [%16 + 6144];\n"
                "min.u32 m, %0, %1;\n min.u32 m, m, %2;\n min.u32 m, m, %3;\n min.u32 m, m, %4;\n min.u32 m, m, %5;\n"
                "min.u32 m, m, %6;\n min.u32 m, m, %7;\n min.u32 m, m, %8;\n min.u32 m, m, %9;\n min.u32 m, m, %10;\n"
                "min.u32 m, m, %11;\n min.u32 m, m, %12;\n min.u32 m, m, %13;\n min.u32 m, m, %14;\n min.u32 m, m, %15;\n"
                "add.u32 n, n, 1;\n"
                "setp.eq.u32 p, m, 0;\n"
                "setp.lt.and.u32 p, n, 5000000, p;\n"
                "vote.sync.any.pred p, p, 0xffffffff;\n"
                "@p bra.uni CHK_%=;\n}"
                : "+r"(w[0]), "+r"(w[1]), "+r"(w[2]), "+r"(w[3]), "+r"(w[4]), "+r"(w[5]), "+r"(w[6]), "+r"(w[7]),
                  "+r"(w[8]), "+r"(w[9]), "+r"(w[10]), "+r"(w[11]), "+r"(w[12]), "+r"(w[13]), "+r"(w[14]), "+r"(w[15])
                : "l"(wsrc + kc * 512), "r"(zero) : "memory");
        };
        const uint32_t stage = sbase + OFF_WOUT + wg * WOUT_SLICE + 2 * 8192;
        const uint32_t st_addr = stage + (((lane >> 4) * 8 + (lane & 7)) << 7)
                               + (((((warp & 3) << 1) | ((lane >> 3) & 1)) ^ (lane & 7)) << 4);
        auto publish = [&](int s) {
            if (pair == (NJOBS + s) % npair) {
                uint32_t a[4];
                asm volatile("ldmatrix.sync.aligned.m8n8.x4.trans.shared.b16 {%0, %1, %2, %3}, [%4];"
                             : "=r"(a[0]), "=r"(a[1]), "=r"(a[2]), "=r"(a[3]) : "r"(st_addr + s * 8192) : "memory");
                asm volatile("st.relaxed.gpu.global.v4.u32 [%0], {%1, %2, %3, %4};" ::"l"(wsrc + (24 + s) * 128),
                             "r"(enc_neg(a[0])), "r"(enc_neg(a[1])), "r"(enc_neg(a[2])), "r"(enc_neg(a[3])) : "memory");
            }
        };
        CHUNK(0, COARSE);
        CHUNK(1, COARSE);
        CHUNK(2, COARSE);
        publish(0);
        load_w(0);
        CHUNK(3, COARSE);
        publish(1);
        load_w(1);
        CHUNK(4, COARSE);
        publish(2);
        load_w(2);
        CHUNK(5, COARSE);
        publish(3);
        wg_wait<0>();
        release<5>(cx);
        pack_q();

        auto flush_part = [&](int row, int part, bool on = true) {
            if (part == 0) {
                asm volatile("fence.proxy.async.shared::cta;" ::: "memory");
                named_bar(wg);
            }
            if (wtid == 0 && on) {
                tma_store_2d(&tm_out, cb * 64, row + (part >> 1) * HW + (part & 1) * 16, stage + part * 8192, POLICY_EVICT_FIRST);
                if (part == 3) asm volatile("cp.async.bulk.commit_group;" ::: "memory");
            }
        };
        auto init_acc = [&](int t) {
#pragma unroll
            for (int b = 0; b < 2; b++) {
#pragma unroll
                for (int h = 0; h < 2; h++) {
                    const uint32_t q = qp[t * 4 + b * 2 + h];
                    const float lo = __uint_as_float(q << 16), hi = __uint_as_float(q & 0xffff0000u);
#pragma unroll
                    for (int dy = 0; dy < 2; dy++) {
                        acc[16 * dy + 8 * b + 2 * h]         = dy ? dup<1>(lo, one) : lo;
                        acc[16 * dy + 8 * b + 2 * h + 1]     = dy ? dup<2>(lo, one) : dup<0>(lo, one);
                        acc[16 * dy + 8 * b + 4 + 2 * h]     = dy ? dup<1>(hi, one) : hi;
                        acc[16 * dy + 8 * b + 4 + 2 * h + 1] = dy ? dup<2>(hi, one) : dup<0>(hi, one);
                    }
                }
            }
        };
        auto stage_tile = [&](int slot) {
            if (wtid == 0) asm volatile("cp.async.bulk.wait_group.read 0;" ::: "memory");
            named_bar(wg);
            wg_wait<0>();
            if (cx.signal) mbar_arrive_cluster(cx.empty_tgt + slot * 8);
#pragma unroll
            for (int i = 0; i < 8; i += 2) {
                stsm_x4_t(st_addr + i * 4096,
                          pack_bf16(acc[4 * i + 0], acc[4 * i + 1]), pack_bf16(acc[4 * i + 2], acc[4 * i + 3]),
                          pack_bf16(acc[4 * i + 4], acc[4 * i + 5]), pack_bf16(acc[4 * i + 6], acc[4 * i + 7]));
            }
        };

        auto load_wo = [&]() {
#pragma unroll
            for (int s = 0; s < 4; s++) {
                asm volatile("ld.global.ca.v4.u32 {%0, %1, %2, %3}, [%4];"
                             : "=r"(qp[4 * s]), "=r"(qp[4 * s + 1]), "=r"(qp[4 * s + 2]), "=r"(qp[4 * s + 3])
                             : "l"(wsrc + (24 + s) * 128) : "memory");
            }
        };

        init_acc(0);
        check_w(0);
        load_w(3);
        load_w(4);
        CHUNK(6, FINE);
        check_w(1);
        CHUNK(7, FINE);
        check_w(2);
        CHUNK(8, FINE);
        check_w(3);
        load_w(5);
        CHUNK(9, FINE);
        check_w(4);
        CHUNK(10, FINE);
        check_w(5);
        CHUNK(11, FINE);

        int seg = pair;
        int prow = seg_row(seg);
        while (true) {
            stage_tile(slot_of<11>());
            init_acc(1);
            CHUNK(12, FINE);
            flush_part(prow, 0);
            CHUNK(13, FINE);
            CHUNK(14, FINE);
            flush_part(prow, 1);
            CHUNK(15, FINE);
            flush_part(prow, 2);
            CHUNK(16, FINE);
            flush_part(prow, 3);
            CHUNK(17, FINE);
            seg += npair;
            prow = seg_row(seg);
            stage_tile(slot_of<17>());
            init_acc(2);
            CHUNK(18, FINE);
            flush_part(prow, 0);
            CHUNK(19, FINE);
            CHUNK(20, FINE);
            flush_part(prow, 1);
            CHUNK(21, FINE);
            flush_part(prow, 2);
            CHUNK(22, FINE);
            flush_part(prow, 3);
            CHUNK(23, FINE);
            seg += npair;
            prow = seg_row(seg);
            stage_tile(slot_of<23>());
            init_acc(3);
            CHUNK(24, FINE);
            flush_part(prow, 0);
            CHUNK(25, FINE);
            load_wo();
            CHUNK(26, FINE);
            flush_part(prow, 1);
            CHUNK(27, FINE);
            flush_part(prow, 2);
            CHUNK(28, FINE);
            flush_part(prow, 3);
            CHUNK(29, FINE);
            seg += npair;
            prow = seg_row(seg);
            const bool tail = seg + 5 * npair >= NSEG;
            stage_tile(slot_of<29>());
            CHUNK(30, COARSE);
            flush_part(prow, 0, !tail);
            CHUNK(31, COARSE);
            check_w(6);
            CHUNK(32, COARSE_REG);
            CHUNK(33, COARSE_REG);
            flush_part(prow, 1, !tail);
            CHUNK(34, COARSE_REG);
            CHUNK(35, COARSE_REG);
            if (tail) break;
            wg_wait<0>();
            release<35>(cx);
            pack_q();
            init_acc(0);
            CHUNK(36, FINE);
            flush_part(prow, 2);
            CHUNK(37, FINE);
            CHUNK(38, FINE);
            CHUNK(39, FINE);
            flush_part(prow, 3);
            CHUNK(40, FINE);
            CHUNK(41, FINE);
            seg += npair;
            prow = seg_row(seg);
            pu ^= 1;
        }
#undef CHUNK

        wg_wait<0>();
        release<35>(cx);
        pack_q();
        auto send = [&](auto mc) {
            constexpr int m = decltype(mc)::v, off = piece_off(m);
            if (m % 4 == 0 && m > 0) prow = seg_row(seg + (m / 4) * npair);
            if (wtid == 0)
                tma_store_2d(&tm_out, cb * 64, prow + (m / 2 % 2) * HW + (m % 2) * 16, stage - 16384 + off, POLICY_EVICT_FIRST);
        };
        auto after = [&](auto tc, auto pc) {
            constexpr int t = decltype(tc)::v, pos = decltype(pc)::v, m = sched_sent(t, pos), n = sched_sent(t, pos + 1) - m;
            if (pos == 0 && t > 1) {
                asm volatile("fence.proxy.async.shared::cta;" ::: "memory");
                named_bar(wg);
            }
            if (n > 0) send(IC<m>{});
        };
        auto stage_piece = [&](auto mc) {
            constexpr int off = piece_off(decltype(mc)::v), i = decltype(mc)::v % 4 * 8;
            stsm_x4_t(st_addr - 16384 + off, pack_bf16(acc[i + 0], acc[i + 1]), pack_bf16(acc[i + 2], acc[i + 3]),
                                             pack_bf16(acc[i + 4], acc[i + 5]), pack_bf16(acc[i + 6], acc[i + 7]));
        };
#define TCHUNK(T, K) chunk<30 + 6 * T + K, FINE, true>(acc, W, qp, zero, cx, pu, ready, wg); after(IC<T>{}, IC<K>{});
#define TAIL_TILE(T)                                                                                          \
        init_acc(T - 1);                                                                                      \
        TCHUNK(T, 0) TCHUNK(T, 1) TCHUNK(T, 2) TCHUNK(T, 3) TCHUNK(T, 4) TCHUNK(T, 5)                         \
        wg_wait<0>();                                                                                         \
        release<35 + 6 * T>(cx);                                                                              \
        stage_piece(IC<4 * T>{}); stage_piece(IC<4 * T + 1>{}); stage_piece(IC<4 * T + 2>{}); stage_piece(IC<4 * T + 3>{});
        TAIL_TILE(1) TAIL_TILE(2) TAIL_TILE(3) TAIL_TILE(4)
#undef TAIL_TILE
#undef TCHUNK
        after(IC<5>{}, IC<0>{});
        send(IC<16>{}); send(IC<17>{}); send(IC<18>{}); send(IC<19>{});
        if (wtid == 0) asm volatile("cp.async.bulk.commit_group;" ::: "memory");
        if (wtid == 0) asm volatile("cp.async.bulk.wait_group.read 0;" ::: "memory");
    } else {
        asm volatile("setmaxnreg.dec.sync.aligned.u32 32;");
        if (warp == 12) {
            asm volatile("bar.sync 5, 448;" ::: "memory");
            if (elect_one()) {
                const int g1 = (pair + 1) % 3, g2 = (pair + 2) % 3;
#pragma unroll 1
                for (int kc = 0; kc < 6; kc++) {
                    const uint32_t bar = sbase + OFF_FULL + (3 + kc) * 8;
                    mbar_expect_tx(bar, (kc & 1) ? SLOT_BYTES : 5 * SLOT_BYTES);
                    tma_load_5d(sbase + OFF_RING + (3 + kc) * SLOT_BYTES, &tm_p8, kc * 64, pair * 2, 0, bar);
                    if (!(kc & 1)) {
                        tma_load_2d(sbase + OFF_WOUT + g1 * WOUT_SLICE + kc * 8192, &tm_wo, rank * 192 + g1 * 64, kc * 64, bar);
                        tma_load_2d(sbase + OFF_WOUT + g2 * WOUT_SLICE + kc * 8192, &tm_wo, rank * 192 + g2 * 64, kc * 64, bar);
                    }
                }
            }
            __syncwarp();
        }
        asm volatile("barrier.cluster.wait.aligned;" ::: "memory");
        if (warp == 12) {
            if ((sbase & 0x3FFFFu) != SMEM_BASE) asm volatile("trap;");
            const uint32_t dst0 = sbase + OFF_RING + rank * 4096;
            uint32_t so = 9 * 8, ph = 1, step = 6;
            auto next_slot = [&]() {
                so += 8;
                if (so == NSLOTS * 8) { so = 0; ph ^= 1; }
            };
            unsigned mytiles = 0, seen = 0;
            auto look = [&]() {
                asm volatile("ld.relaxed.gpu.global.u32 %0, [%1];" : "=r"(seen) : "l"(&scr->prog) : "memory");
            };
            auto tile = [&](bool coarse, int coord, uint64_t pol, bool last) {
                if (rank == 0 && mytiles >= GOV_START) {
                    const unsigned need = mytiles * npair - 2 * max(GOV_TIGHT - (int)mytiles, 0);
                    unsigned spins = 0;
                    while (__any_sync(0xffffffffu, (int)(need - seen) > 0) && ++spins < 100000u) look();
                }
                mytiles++;
#pragma unroll
                for (int kc = 0; kc < 6; kc++) {
                    const uint32_t bar = sbase + OFF_FULL + so, dst = dst0 + so * (SLOT_BYTES / 8);
                    mbar_wait_bounded(sbase + OFF_EMPTY + so, ph);
                    step++;
                    if (elect_one()) {
                        mbar_expect_tx(bar, SLOT_BYTES);
                        if (coarse) tma_load_5d_mc(dst, &tm_p, kc * 64, pair * 2, coord, bar, pol);
                        else        tma_load_2d_mc(dst, &tm_c, kc * 64, coord, bar, pol);
                        asm volatile("st.volatile.shared.u32 [%0], %1;" ::"r"(sbase + OFF_PACE), "r"(step) : "memory");
                    }
                    if (kc == 0 && rank == 0 && lane == 0 && !last)
                        asm volatile("red.relaxed.gpu.global.add.u32 [%0], 1;" ::"l"(&scr->prog) : "memory");
                    next_slot();
                    if (kc == 3 && rank == 0) look();
                }
            };
            const int ntiles = nfine + nfine / 4;
#pragma unroll 1
            for (int i = 1; i < ntiles; i++) {
                int j;
                const bool coarse = tile_of(i, j);
                tile(coarse, coarse ? j + 2 * rank : seg_row(j * npair + pair) + rank * HW,
                     i >= ntiles - EF_TILES ? POLICY_EVICT_FIRST : POLICY_EVICT_NORMAL, i + 1 == ntiles);
            }
            if (rank == 0 && lane == 0) {
                if (atomicAdd(&scr->prog, 1u) + 1 == mytiles * npair) {
                    asm volatile("st.relaxed.gpu.global.u32 [%0], 0;" ::"l"(&scr->prog) : "memory");
                    asm volatile("red.relaxed.gpu.global.add.u32 [%0], 1;" ::"l"(&scr->epoch) : "memory");
                }
            }
            __syncwarp();
#pragma unroll 1
            for (int s = 0; s < NSLOTS; s++) {
                mbar_wait_bounded(sbase + OFF_EMPTY + so, ph);
                next_slot();
            }
        } else if (warp == 13) {
            auto wait_pace = [&](int need) {
                unsigned spins = 0;
                while (true) {
                    uint32_t v;
                    asm volatile("ld.volatile.shared.u32 %0, [%1];" : "=r"(v) : "r"(sbase + OFF_PACE) : "memory");
                    if ((int)v >= need || ++spins > 4000000u) break;
                    __nanosleep(20);
                }
            };
            if (lane == 0) mbar_expect_tx(sbase + OFF_NB, 12 * 512);
#pragma unroll 1
            for (int k = 0; k < 12; k++) {
                const int j = k < 6 ? 2 : 3;
                wait_pace(PF_FIRST + k * 3 / 4);
                if (lane == 0)
                    tma_load_2d(sbase + OFF_SINK, &tm_cf, 0, (seg_row(j * npair + pair) + rank * HW) * 6 + (k - (j - 2) * 6) * 32,
                                sbase + OFF_NB);
            }
#pragma unroll 1
            for (int i = 5; i < nfine + nfine / 4; i++) {
                int j;
                const char *b0, *b1;
                if (tile_of(i, j)) {
                    b0 = (const char*)p_ptr + (size_t)((j + 2 * rank) * npair + pair) * (16 * C * 2);
                    b1 = b0 + (size_t)npair * (16 * C * 2);
                } else {
                    b0 = (const char*)c_ptr + (size_t)(seg_row(j * npair + pair) + rank * HW) * (C * 2);
                    b1 = b0 + 16 * C * 2;
                }
                wait_pace(6 * i - max(PF_LEAD0 - max(i - PF_DECAY, 0), PF_LEAD));
#pragma unroll
                for (int k = 0; k < 6; k++) {
                    asm volatile("prefetch.global.L2 [%0];" ::"l"((k < 3 ? b0 : b1) + lane * 128 + (k % 3) * 4096) : "memory");
                    __nanosleep(PF_GAP);
                }
            }
            mbar_wait_bounded(sbase + OFF_NB, 0);
        } else if (warp == 15) {
            uint32_t par;
            asm volatile("ld.relaxed.gpu.global.u32 %0, [%1];" : "=r"(par) : "l"(&scr->epoch) : "memory");
            uint4* clr = scr->wfrag + (~par & 1) * (6 * NFRAG * 128);
#pragma unroll 1
            for (int i = blockIdx.x * 32 + lane; i < 6 * NFRAG * 128; i += npair * 64) clr[i] = make_uint4(0u, 0u, 0u, 0u);
        }
    }
}

typedef CUresult (*EncodeFn)(CUtensorMap*, CUtensorMapDataType, cuuint32_t, void*, const cuuint64_t*, const cuuint64_t*,
                             const cuuint32_t*, const cuuint32_t*, CUtensorMapInterleave, CUtensorMapSwizzle,
                             CUtensorMapL2promotion, CUtensorMapFloatOOBfill);

void encode(EncodeFn fn, CUtensorMap* tm, const void* ptr, int rank, const cuuint64_t* dims, const cuuint64_t* strides,
            const cuuint32_t* box, CUtensorMapSwizzle swizzle = CU_TENSOR_MAP_SWIZZLE_128B,
            CUtensorMapL2promotion promotion = CU_TENSOR_MAP_L2_PROMOTION_NONE) {
    const cuuint32_t es[5] = {1, 1, 1, 1, 1};
    fn(tm, CU_TENSOR_MAP_DATA_TYPE_BFLOAT16, (cuuint32_t)rank, const_cast<void*>(ptr), dims, strides, box, es,
       CU_TENSOR_MAP_INTERLEAVE_NONE, swizzle, promotion, CU_TENSOR_MAP_FLOAT_OOB_FILL_NONE);
}

}

extern "C" void kernel_launch(void* const* d_in, const int* in_sizes, int n_in, void* d_out, int out_size) {
    (void)in_sizes; (void)n_in; (void)out_size;
    const __nv_bfloat16* c_fine   = (const __nv_bfloat16*)d_in[0];
    const __nv_bfloat16* p_coarse = (const __nv_bfloat16*)d_in[1];
    const __nv_bfloat16* w_lat    = (const __nv_bfloat16*)d_in[2];
    const __nv_bfloat16* w_out    = (const __nv_bfloat16*)d_in[3];

    static EncodeFn fn = nullptr;
    static int np = 0;
    static Scratch* scr = nullptr;
    if (!fn) {
        void* p = nullptr;
        cudaDriverEntryPointQueryResult qr;
        cudaGetDriverEntryPoint("cuTensorMapEncodeTiled", &p, cudaEnableDefault, &qr);
        fn = (EncodeFn)p;
        cudaGetSymbolAddress((void**)&scr, g_scratch);
        cudaFuncSetAttribute(fpn_kernel<NPAIRS>, cudaFuncAttributeMaxDynamicSharedMemorySize, SMEM_BYTES);
        cudaFuncSetAttribute(fpn_kernel<0>, cudaFuncAttributeMaxDynamicSharedMemorySize, SMEM_BYTES);
        cudaLaunchConfig_t cfg = {};
        cfg.gridDim = dim3(2); cfg.blockDim = dim3(NTHREADS); cfg.dynamicSmemBytes = SMEM_BYTES;
        cudaLaunchAttribute at[1];
        at[0].id = cudaLaunchAttributeClusterDimension;
        at[0].val.clusterDim.x = 2; at[0].val.clusterDim.y = 1; at[0].val.clusterDim.z = 1;
        cfg.attrs = at; cfg.numAttrs = 1;
        if (cudaOccupancyMaxActiveClusters(&np, fpn_kernel<0>, &cfg) != cudaSuccess || np < 1) np = 1;
        if (np > NPAIRS) np = NPAIRS;
        while ((NSEG / 4) % np) np--;
    }

    CUtensorMap tm_cf, tm_c, tm_p, tm_wl3, tm_out, tm_p8, tm_wo;
    {
        const cuuint64_t dims[2] = {(cuuint64_t)C, (cuuint64_t)NPIX};
        const cuuint64_t str[1]  = {(cuuint64_t)C * 2};
        const cuuint32_t box_in[2]  = {64, 32};
        const cuuint32_t box_out[2] = {64, 16};
        encode(fn, &tm_c, c_fine, 2, dims, str, box_in);
        encode(fn, &tm_out, d_out, 2, dims, str, box_out);
    }
    {
        const cuuint64_t dims[5] = {(cuuint64_t)C, 2, 4, (cuuint64_t)(2 * np), (cuuint64_t)(NSEG / np)};
        const cuuint64_t str[4]  = {(cuuint64_t)4 * C * 2, (cuuint64_t)C * 2, (cuuint64_t)8 * C * 2, (cuuint64_t)np * 16 * C * 2};
        const cuuint32_t box[5]  = {64, 2, 4, 2, 2};
        encode(fn, &tm_p, p_coarse, 5, dims, str, box);
        const cuuint32_t box8[5] = {64, 2, 4, 2, 4};
        encode(fn, &tm_p8, p_coarse, 5, dims, str, box8);
    }
    {
        const cuuint64_t dims[2] = {(cuuint64_t)C, (cuuint64_t)C};
        const cuuint64_t str[1]  = {(cuuint64_t)C * 2};
        const cuuint32_t box[2] = {64, 128};
        encode(fn, &tm_wo, w_out, 2, dims, str, box);
    }
    {
        const cuuint64_t dims[3] = {64, (cuuint64_t)C, 6};
        const cuuint64_t str[2]  = {(cuuint64_t)C * 2, 128};
        const cuuint32_t box[3]  = {64, 32, 2};
        encode(fn, &tm_wl3, w_lat, 3, dims, str, box);
    }
    {
        const cuuint64_t dims[2] = {64, (cuuint64_t)NPIX * 6};
        const cuuint64_t str[1]  = {128};
        const cuuint32_t box[2]  = {8, 32};
        encode(fn, &tm_cf, c_fine, 2, dims, str, box, CU_TENSOR_MAP_SWIZZLE_NONE, CU_TENSOR_MAP_L2_PROMOTION_L2_128B);
    }
    auto kernel = np == NPAIRS ? fpn_kernel<NPAIRS> : fpn_kernel<0>;
    kernel<<<2 * np, NTHREADS, SMEM_BYTES>>>(scr, c_fine, p_coarse, NSEG / np, 1.0f, 0u,
                                             tm_wo, tm_wl3, tm_p8, tm_c, tm_p, tm_out, tm_cf);
}
```
